```python
import torch

def _softmax(x, axis=-1):
    return torch.softmax(x, dim=axis)
def _gelu(x):
    return torch.nn.functional.gelu(x, approximate="tanh")
def _silu(x):
    return torch.nn.functional.silu(x)
def _sigmoid(x):
    return torch.sigmoid(x)
def _layernorm(x, axis=-1, eps=1e-5):
    m = x.mean(dim=axis, keepdim=True)
    v = x.var(dim=axis, keepdim=True, unbiased=False)
    return (x - m) / torch.sqrt(v + eps)
def _scatter_add(tgt, idx, src, axis=0):
    return tgt.clone().index_add_(axis, idx, src)
def _segment_sum(src, seg, n):
    out = torch.zeros((n,) + src.shape[1:], dtype=src.dtype)
    return out.index_add_(0, seg, src)
def _pad(x, pw):
    flat = tuple(v for pair in reversed(pw) for v in pair)
    return torch.nn.functional.pad(x, flat)

kernel_name = 'standalone__groupnorm__prompt'

def setup_inputs():

    _w = (lambda a: (lambda t: t.to(torch.bfloat16) if t.is_floating_point() else t)(torch.as_tensor(a)))
    B = 1
    G = 32
    cpg = max(1, 448 // G)
    C = G * cpg
    H, W = 16, 4096
    return {
        "x": _w(abs((lambda *s: torch.randn(*s, dtype=torch.bfloat16) * 0.05)(B, C, H, W))),
        "g": _w((lambda *s: torch.randn(*s, dtype=torch.bfloat16) * 0.05)(C) + 1.0),
        "b": _w((lambda *s: torch.randn(*s, dtype=torch.bfloat16) * 0.4)(C)),
    }

def reference(x, g, b):
    G = 32
    B, C, H, W = x.shape[0], x.shape[1], x.shape[2], x.shape[3]
    xr = x.reshape(B, G, C // G, H, W)
    mu = xr.mean(axis=(2, 3, 4), keepdims=True)
    var = ((xr - mu) ** 2).mean(axis=(2, 3, 4), keepdims=True)
    xn = (xr - mu) / torch.sqrt(var + 1e-5)
    xn = xn.reshape(B, C, H, W)
    return xn * g[None, :, None, None] + b[None, :, None, None]
```

```cpp
#include <cuda_runtime.h>
#include <cuda_bf16.h>
#include <stdint.h>

namespace gn {

constexpr int G = 32;
constexpr int C = 448;
constexpr int CPG = C / G;
constexpr int HW = 16 * 4096;
constexpr int HW_SHIFT = 16;
constexpr long long GROUP_ELEMS = (long long)CPG * HW;
constexpr int UNIT_BYTES = 128;
constexpr int GROUP_UNITS = (int)(GROUP_ELEMS * 2 / UNIT_BYTES);
constexpr int MAX_CTAS = 512;
constexpr int MAX_SLOTS = 16;

constexpr int GATHER_WARPS = 2;
constexpr int STATS_WARPS = 4;
constexpr int NORM_WARPS = 8;
constexpr int NUM_WARPS = 1 + GATHER_WARPS + STATS_WARPS + NORM_WARPS;
constexpr int NTHREADS = NUM_WARPS * 32;
constexpr int STATS_THREADS = STATS_WARPS * 32;
constexpr int NORM_THREADS = NORM_WARPS * 32;
constexpr unsigned SPIN_LIMIT = 1u << 24;

__device__ float2 g_part[G][MAX_CTAS];
__device__ unsigned int g_cnt[G];
__device__ unsigned int g_done;

__device__ __forceinline__ uint32_t smem_u32(const void* p) {
    return (uint32_t)__cvta_generic_to_shared(p);
}
__device__ __forceinline__ void mbar_init(uint32_t bar, uint32_t count) {
    asm volatile("mbarrier.init.shared::cta.b64 [%0], %1;" ::"r"(bar), "r"(count) : "memory");
}
__device__ __forceinline__ void mbar_arrive_expect_tx(uint32_t bar, uint32_t bytes) {
    asm volatile("mbarrier.arrive.expect_tx.shared::cta.b64 _, [%0], %1;" ::"r"(bar), "r"(bytes)
                 : "memory");
}
__device__ __forceinline__ void mbar_arrive(uint32_t bar) {
    asm volatile("mbarrier.arrive.shared::cta.b64 _, [%0];" ::"r"(bar) : "memory");
}
__device__ __forceinline__ bool mbar_try_wait(uint32_t bar, uint32_t parity) {
    uint32_t ok;
    asm volatile(
        "{\n\t.reg .pred p;\n\t"
        "mbarrier.try_wait.parity.shared::cta.b64 p, [%1], %2;\n\t"
        "selp.u32 %0, 1, 0, p;\n\t}"
        : "=r"(ok)
        : "r"(bar), "r"(parity)
        : "memory");
    return ok != 0;
}
__device__ __forceinline__ void mbar_wait(uint32_t bar, uint32_t parity) {
    unsigned it = 0;
    while (!mbar_try_wait(bar, parity)) {
        if (++it > SPIN_LIMIT) break;
    }
}
__device__ __forceinline__ unsigned ld_acquire_u32(const unsigned* p) {
    unsigned v;
    asm volatile("ld.acquire.gpu.global.u32 %0, [%1];" : "=r"(v) : "l"(p) : "memory");
    return v;
}
__device__ __forceinline__ void red_release_add_u32(unsigned* p, unsigned v) {
    asm volatile("red.release.gpu.global.add.u32 [%0], %1;" ::"l"(p), "r"(v) : "memory");
}
__device__ __forceinline__ void bulk_load(uint32_t dst, const void* src, uint32_t bytes, uint32_t bar,
                                          uint64_t policy) {
    asm volatile(
        "cp.async.bulk.shared::cluster.global.mbarrier::complete_tx::bytes.L2::cache_hint "
        "[%0], [%1], %2, [%3], %4;" ::"r"(dst), "l"(src), "r"(bytes), "r"(bar), "l"(policy)
        : "memory");
}

struct Stat {
    float n, mean, m2;
};
__device__ __forceinline__ Stat merge(const Stat a, const Stat b) {
    Stat r;
    r.n = a.n + b.n;
    const float w = (r.n > 0.f) ? __fdividef(b.n, r.n) : 0.f;
    const float d = b.mean - a.mean;
    r.mean = fmaf(d, w, a.mean);
    r.m2 = a.m2 + b.m2 + d * d * a.n * w;
    return r;
}
__device__ __forceinline__ Stat warp_merge(Stat s) {
#pragma unroll
    for (int off = 16; off >= 1; off >>= 1) {
        Stat o;
        o.n = __shfl_xor_sync(0xffffffffu, s.n, off);
        o.mean = __shfl_xor_sync(0xffffffffu, s.mean, off);
        o.m2 = __shfl_xor_sync(0xffffffffu, s.m2, off);
        s = merge(s, o);
    }
    return s;
}

__device__ __forceinline__ float bf_lo(uint32_t u) { return __uint_as_float(u << 16); }
__device__ __forceinline__ float bf_hi(uint32_t u) { return __uint_as_float(u & 0xffff0000u); }
__device__ __forceinline__ uint32_t pack_bf16(float lo, float hi) {
    uint32_t r;
    asm("cvt.rn.bf16x2.f32 %0, %1, %2;" : "=r"(r) : "f"(hi), "f"(lo));
    return r;
}

__global__ void __launch_bounds__(NTHREADS, 1)
gn_kernel(const __nv_bfloat16* __restrict__ x, const __nv_bfloat16* __restrict__ gamma,
          const __nv_bfloat16* __restrict__ beta, __nv_bfloat16* __restrict__ out, int nslots,
          int slot_bytes) {
    extern __shared__ __align__(1024) unsigned char smem[];
    unsigned char* tail = smem + (size_t)nslots * slot_bytes;
    uint64_t* bar_full = reinterpret_cast<uint64_t*>(tail);
    uint64_t* bar_empty = bar_full + MAX_SLOTS;
    uint64_t* bar_ready = bar_empty + MAX_SLOTS;
    float2* s_stat = reinterpret_cast<float2*>(bar_ready + G);
    float* s_gamma = reinterpret_cast<float*>(s_stat + G);
    float* s_beta = s_gamma + C;
    float* s_scratch = s_beta + C;

    const int tid = threadIdx.x;
    const int warp = tid >> 5;
    const int lane = tid & 31;
    const int cta = blockIdx.x;
    const int ncta = gridDim.x;

    const int base = GROUP_UNITS / ncta;
    const int rem = GROUP_UNITS - base * ncta;
    const int my_units = base + (cta < rem ? 1 : 0);
    const int my_start = cta * base + (cta < rem ? cta : rem);
    const uint32_t my_bytes = (uint32_t)my_units * UNIT_BYTES;
    const int nvec = my_units * (UNIT_BYTES / 16);

    if (tid == 0) {
        for (int s = 0; s < nslots; s++) {
            mbar_init(smem_u32(&bar_full[s]), 1);
            mbar_init(smem_u32(&bar_empty[s]), NORM_WARPS);
        }
        for (int j = 0; j < G; j++) mbar_init(smem_u32(&bar_ready[j]), 1);
        asm volatile("fence.mbarrier_init.release.cluster;" ::: "memory");
        asm volatile("fence.proxy.async;" ::: "memory");
    }
    for (int c = tid; c < C; c += NTHREADS) {
        s_gamma[c] = __bfloat162float(gamma[c]);
        s_beta[c] = __bfloat162float(beta[c]);
    }
    __syncthreads();

    if (warp == 0) {
        if (lane == 0) {
            uint64_t policy;
            asm volatile("createpolicy.fractional.L2::evict_first.b64 %0, 1.0;" : "=l"(policy));
            int s = 0;
            uint32_t ph = 0;
            for (int i = 0; i < G; i++) {
                if (i >= nslots) mbar_wait(smem_u32(&bar_empty[s]), ph ^ 1u);
                mbar_arrive_expect_tx(smem_u32(&bar_full[s]), my_bytes);
                const unsigned char* src = reinterpret_cast<const unsigned char*>(x) +
                                           (size_t)i * (GROUP_ELEMS * 2) + (size_t)my_start * UNIT_BYTES;
                bulk_load(smem_u32(smem + (size_t)s * slot_bytes), src, my_bytes,
                          smem_u32(&bar_full[s]), policy);
                if (++s == nslots) { s = 0; ph ^= 1u; }
            }
        }
    } else if (warp <= GATHER_WARPS) {
        const int k = warp - 1;
        for (int j = k; j < G; j += GATHER_WARPS) {
            unsigned it = 0;
            while (ld_acquire_u32(&g_cnt[j]) < (unsigned)ncta) {
                __nanosleep(40);
                if (++it > SPIN_LIMIT) break;
            }
            Stat acc = {0.f, 0.f, 0.f};
            for (int c = lane; c < ncta; c += 32) {
                const float2 p = __ldcg(&g_part[j][c]);
                Stat o;
                o.n = (float)((base + (c < rem ? 1 : 0)) * (UNIT_BYTES / 2));
                o.mean = p.x;
                o.m2 = p.y;
                acc = merge(acc, o);
            }
            acc = warp_merge(acc);
            if (lane == 0) {
                const float var = acc.m2 / acc.n;
                const float rstd = 1.0f / sqrtf(var + 1e-5f);
                s_stat[j] = make_float2(acc.mean, rstd);
                mbar_arrive(smem_u32(&bar_ready[j]));
            }
        }
        __syncwarp();
        if (lane == 0) {
            const unsigned prev = atomicAdd(&g_done, 1u);
            if (prev == (unsigned)(ncta * GATHER_WARPS - 1)) {
                for (int j = 0; j < G; j++) g_cnt[j] = 0u;
                g_done = 0u;
                __threadfence();
            }
        }
    } else if (warp <= GATHER_WARPS + STATS_WARPS) {
        const int sw = warp - 1 - GATHER_WARPS;
        const int t = sw * 32 + lane;
        int s = 0;
        uint32_t ph = 0;
        for (int i = 0; i < G; i++) {
            mbar_wait(smem_u32(&bar_full[s]), ph);
            const uint4* sv = reinterpret_cast<const uint4*>(smem + (size_t)s * slot_bytes);
            float piv = 0.f, s1 = 0.f, s2 = 0.f;
            int cnt = 0;
            for (int v = t; v < nvec; v += STATS_THREADS) {
                const uint4 q = sv[v];
                if (cnt == 0) piv = bf_lo(q.x);
                const uint32_t w4[4] = {q.x, q.y, q.z, q.w};
#pragma unroll
                for (int e = 0; e < 4; e++) {
                    const float d0 = bf_lo(w4[e]) - piv;
                    const float d1 = bf_hi(w4[e]) - piv;
                    s1 += d0;
                    s2 = fmaf(d0, d0, s2);
                    s1 += d1;
                    s2 = fmaf(d1, d1, s2);
                }
                cnt += 8;
            }
            Stat st;
            st.n = (float)cnt;
            const float inv = cnt > 0 ? __fdividef(1.f, (float)cnt) : 0.f;
            const float dm = s1 * inv;
            st.mean = piv + dm;
            st.m2 = fmaxf(s2 - s1 * dm, 0.f);
            st = warp_merge(st);
            float* sc = s_scratch + ((i & 1) * STATS_WARPS) * 4;
            if (lane == 0) {
                sc[sw * 4 + 0] = st.n;
                sc[sw * 4 + 1] = st.mean;
                sc[sw * 4 + 2] = st.m2;
            }
            asm volatile("bar.sync 1, %0;" ::"n"(STATS_THREADS) : "memory");
            if (sw == 0 && lane == 0) {
                Stat a = {sc[0], sc[1], sc[2]};
#pragma unroll
                for (int w = 1; w < STATS_WARPS; w++) {
                    Stat o = {sc[w * 4 + 0], sc[w * 4 + 1], sc[w * 4 + 2]};
                    a = merge(a, o);
                }
                g_part[i][cta] = make_float2(a.mean, a.m2);
                red_release_add_u32(&g_cnt[i], 1u);
            }
            if (++s == nslots) { s = 0; ph ^= 1u; }
        }
    } else {
        const int t = (warp - 1 - GATHER_WARPS - STATS_WARPS) * 32 + lane;
        int s = 0;
        uint32_t ph = 0;
        for (int j = 0; j < G; j++) {
            mbar_wait(smem_u32(&bar_ready[j]), 0u);
            mbar_wait(smem_u32(&bar_full[s]), ph);
            const float2 ms = s_stat[j];
            const long long ge0 = (long long)j * GROUP_ELEMS + (long long)my_start * (UNIT_BYTES / 2);
            const int c0 = (int)(ge0 >> HW_SHIFT);
            const int vb = (int)((((long long)(c0 + 1) << HW_SHIFT) - ge0) >> 3);
            const int c1 = (c0 + 1 < C) ? c0 + 1 : c0;
            const float a0 = ms.y * s_gamma[c0];
            const float d0 = fmaf(-ms.x, a0, s_beta[c0]);
            const float a1 = ms.y * s_gamma[c1];
            const float d1 = fmaf(-ms.x, a1, s_beta[c1]);
            const uint4* sv = reinterpret_cast<const uint4*>(smem + (size_t)s * slot_bytes);
            uint4* dst = reinterpret_cast<uint4*>(out + ge0);
#pragma unroll 4
            for (int v = t; v < nvec; v += NORM_THREADS) {
                const uint4 q = sv[v];
                const float a = (v < vb) ? a0 : a1;
                const float d = (v < vb) ? d0 : d1;
                uint4 r;
                r.x = pack_bf16(fmaf(bf_lo(q.x), a, d), fmaf(bf_hi(q.x), a, d));
                r.y = pack_bf16(fmaf(bf_lo(q.y), a, d), fmaf(bf_hi(q.y), a, d));
                r.z = pack_bf16(fmaf(bf_lo(q.z), a, d), fmaf(bf_hi(q.z), a, d));
                r.w = pack_bf16(fmaf(bf_lo(q.w), a, d), fmaf(bf_hi(q.w), a, d));
                dst[v] = r;
            }
            __syncwarp();
            if (lane == 0) mbar_arrive(smem_u32(&bar_empty[s]));
            if (++s == nslots) { s = 0; ph ^= 1u; }
        }
    }
}

}

extern "C" void kernel_launch(void* const* d_in, const int* in_sizes, int n_in, void* d_out,
                              int out_size) {
    (void)in_sizes; (void)n_in; (void)out_size;
    static int num_sms = 0;
    static int nslots = 0, slot_bytes = 0, smem_bytes = 0;
    if (num_sms == 0) {
        int dev = 0, max_smem = 0;
        cudaGetDevice(&dev);
        cudaDeviceGetAttribute(&num_sms, cudaDevAttrMultiProcessorCount, dev);
        cudaDeviceGetAttribute(&max_smem, cudaDevAttrMaxSharedMemoryPerBlockOptin, dev);
        if (num_sms > gn::MAX_CTAS) num_sms = gn::MAX_CTAS;
        const int max_units = (gn::GROUP_UNITS + num_sms - 1) / num_sms;
        slot_bytes = max_units * gn::UNIT_BYTES;
        const int tail_bytes = (2 * gn::MAX_SLOTS + gn::G) * 8 + gn::G * 8 + 2 * gn::C * 4 +
                               2 * gn::STATS_WARPS * 4 * 4 + 64;
        nslots = (max_smem - tail_bytes) / slot_bytes;
        if (nslots > gn::MAX_SLOTS) nslots = gn::MAX_SLOTS;
        smem_bytes = nslots * slot_bytes + tail_bytes;
        cudaFuncSetAttribute(gn::gn_kernel, cudaFuncAttributeMaxDynamicSharedMemorySize, smem_bytes);
    }
    const __nv_bfloat16* x = (const __nv_bfloat16*)d_in[0];
    const __nv_bfloat16* g = (const __nv_bfloat16*)d_in[1];
    const __nv_bfloat16* b = (const __nv_bfloat16*)d_in[2];
    __nv_bfloat16* out = (__nv_bfloat16*)d_out;
    gn::gn_kernel<<<num_sms, gn::NTHREADS, smem_bytes>>>(x, g, b, out, nslots, slot_bytes);
}
```

```cpp
#include <cuda_runtime.h>
#include <cuda_bf16.h>
#include <stdint.h>

namespace gn {

constexpr int G = 32;
constexpr int C = 448;
constexpr int CPG = C / G;
constexpr int HW = 16 * 4096;
constexpr int HW_SHIFT = 16;
constexpr long long GROUP_ELEMS = (long long)CPG * HW;
constexpr int UNIT_BYTES = 128;
constexpr int GROUP_UNITS = (int)(GROUP_ELEMS * 2 / UNIT_BYTES);
constexpr int MAX_CTAS = 512;
constexpr int MAX_SLOTS = 16;

constexpr int GATHER_WARPS = 4;
constexpr int STATS_WARPS = 4;
constexpr int NORM_WARPS = 8;
constexpr int NUM_WARPS = 1 + GATHER_WARPS + STATS_WARPS + NORM_WARPS;
constexpr int NTHREADS = NUM_WARPS * 32;
constexpr int STATS_THREADS = STATS_WARPS * 32;
constexpr int NORM_THREADS = NORM_WARPS * 32;
constexpr unsigned SPIN_LIMIT = 1u << 24;

__device__ ulonglong2 g_part[G][MAX_CTAS];
__device__ unsigned int g_epoch;
__device__ unsigned int g_done;

__device__ __forceinline__ uint32_t smem_u32(const void* p) {
    return (uint32_t)__cvta_generic_to_shared(p);
}
__device__ __forceinline__ void mbar_init(uint32_t bar, uint32_t count) {
    asm volatile("mbarrier.init.shared::cta.b64 [%0], %1;" ::"r"(bar), "r"(count) : "memory");
}
__device__ __forceinline__ void mbar_arrive_expect_tx(uint32_t bar, uint32_t bytes) {
    asm volatile("mbarrier.arrive.expect_tx.shared::cta.b64 _, [%0], %1;" ::"r"(bar), "r"(bytes)
                 : "memory");
}
__device__ __forceinline__ void mbar_arrive(uint32_t bar) {
    asm volatile("mbarrier.arrive.shared::cta.b64 _, [%0];" ::"r"(bar) : "memory");
}
__device__ __forceinline__ bool mbar_try_wait(uint32_t bar, uint32_t parity) {
    uint32_t ok;
    asm volatile(
        "{\n\t.reg .pred p;\n\t"
        "mbarrier.try_wait.parity.shared::cta.b64 p, [%1], %2;\n\t"
        "selp.u32 %0, 1, 0, p;\n\t}"
        : "=r"(ok)
        : "r"(bar), "r"(parity)
        : "memory");
    return ok != 0;
}
__device__ __forceinline__ void mbar_wait(uint32_t bar, uint32_t parity) {
    unsigned it = 0;
    while (!mbar_try_wait(bar, parity)) {
        if (++it > SPIN_LIMIT) break;
    }
}
__device__ __forceinline__ ulonglong2 ld_relaxed_v2(const ulonglong2* p) {
    ulonglong2 v;
    asm volatile("ld.relaxed.gpu.global.v2.b64 {%0, %1}, [%2];" : "=l"(v.x), "=l"(v.y) : "l"(p) : "memory");
    return v;
}
__device__ __forceinline__ void st_relaxed_v2(ulonglong2* p, ulonglong2 v) {
    asm volatile("st.relaxed.gpu.global.v2.b64 [%0], {%1, %2};" ::"l"(p), "l"(v.x), "l"(v.y) : "memory");
}
__device__ __forceinline__ void bulk_load(uint32_t dst, const void* src, uint32_t bytes, uint32_t bar,
                                          uint64_t policy) {
    asm volatile(
        "cp.async.bulk.shared::cluster.global.mbarrier::complete_tx::bytes.L2::cache_hint "
        "[%0], [%1], %2, [%3], %4;" ::"r"(dst), "l"(src), "r"(bytes), "r"(bar), "l"(policy)
        : "memory");
}

struct Stat {
    float n, mean, m2;
};
__device__ __forceinline__ Stat merge(const Stat a, const Stat b) {
    Stat r;
    r.n = a.n + b.n;
    const float w = (r.n > 0.f) ? __fdividef(b.n, r.n) : 0.f;
    const float d = b.mean - a.mean;
    r.mean = fmaf(d, w, a.mean);
    r.m2 = a.m2 + b.m2 + d * d * a.n * w;
    return r;
}
__device__ __forceinline__ Stat warp_merge(Stat s) {
#pragma unroll
    for (int off = 16; off >= 1; off >>= 1) {
        Stat o;
        o.n = __shfl_xor_sync(0xffffffffu, s.n, off);
        o.mean = __shfl_xor_sync(0xffffffffu, s.mean, off);
        o.m2 = __shfl_xor_sync(0xffffffffu, s.m2, off);
        s = merge(s, o);
    }
    return s;
}

__device__ __forceinline__ float bf_lo(uint32_t u) { return __uint_as_float(u << 16); }
__device__ __forceinline__ float bf_hi(uint32_t u) { return __uint_as_float(u & 0xffff0000u); }
__device__ __forceinline__ uint32_t pack_bf16(float lo, float hi) {
    uint32_t r;
    asm("cvt.rn.bf16x2.f32 %0, %1, %2;" : "=r"(r) : "f"(hi), "f"(lo));
    return r;
}

__global__ void __launch_bounds__(NTHREADS, 1)
gn_kernel(const __nv_bfloat16* __restrict__ x, const __nv_bfloat16* __restrict__ gamma,
          const __nv_bfloat16* __restrict__ beta, __nv_bfloat16* __restrict__ out, int nslots,
          int slot_bytes) {
    extern __shared__ __align__(1024) unsigned char smem[];
    unsigned char* tail = smem + (size_t)nslots * slot_bytes;
    uint64_t* bar_full = reinterpret_cast<uint64_t*>(tail);
    uint64_t* bar_empty = bar_full + MAX_SLOTS;
    uint64_t* bar_ready = bar_empty + MAX_SLOTS;
    uint64_t* bar_stats = bar_ready + G;
    float2* s_stat = reinterpret_cast<float2*>(bar_stats + G);
    float* s_gamma = reinterpret_cast<float*>(s_stat + G);
    float* s_beta = s_gamma + C;
    float* s_scratch = s_beta + C;

    const int tid = threadIdx.x;
    const int warp = tid >> 5;
    const int lane = tid & 31;
    const int cta = blockIdx.x;
    const int ncta = gridDim.x;

    const int base = GROUP_UNITS / ncta;
    const int rem = GROUP_UNITS - base * ncta;
    const int my_units = base + (cta < rem ? 1 : 0);
    const int my_start = cta * base + (cta < rem ? cta : rem);
    const uint32_t my_bytes = (uint32_t)my_units * UNIT_BYTES;
    const int nvec = my_units * (UNIT_BYTES / 16);

    if (tid == 0) {
        for (int s = 0; s < nslots; s++) {
            mbar_init(smem_u32(&bar_full[s]), 1);
            mbar_init(smem_u32(&bar_empty[s]), NORM_WARPS);
        }
        for (int j = 0; j < G; j++) {
            mbar_init(smem_u32(&bar_ready[j]), 1);
            mbar_init(smem_u32(&bar_stats[j]), STATS_WARPS);
        }
        asm volatile("fence.mbarrier_init.release.cluster;" ::: "memory");
        asm volatile("fence.proxy.async;" ::: "memory");
    }
    for (int c = tid; c < C; c += NTHREADS) {
        s_gamma[c] = __bfloat162float(gamma[c]);
        s_beta[c] = __bfloat162float(beta[c]);
    }
    __syncthreads();

    if (warp == 0) {
        if (lane == 0) {
            uint64_t policy;
            asm volatile("createpolicy.fractional.L2::evict_first.b64 %0, 1.0;" : "=l"(policy));
            int s = 0;
            uint32_t ph = 0;
            for (int i = 0; i < G; i++) {
                if (i >= nslots) mbar_wait(smem_u32(&bar_empty[s]), ph ^ 1u);
                mbar_arrive_expect_tx(smem_u32(&bar_full[s]), my_bytes);
                const unsigned char* src = reinterpret_cast<const unsigned char*>(x) +
                                           (size_t)i * (GROUP_ELEMS * 2) + (size_t)my_start * UNIT_BYTES;
                bulk_load(smem_u32(smem + (size_t)s * slot_bytes), src, my_bytes,
                          smem_u32(&bar_full[s]), policy);
                if (++s == nslots) { s = 0; ph ^= 1u; }
            }
        }
    } else if (warp <= GATHER_WARPS) {
        const int k = warp - 1;
        const unsigned long long tag = (unsigned long long)(*(volatile unsigned int*)&g_epoch) + 1ull;
        const unsigned long long tag_hi = tag << 32;
        for (int j = k; j < G; j += GATHER_WARPS) {
            mbar_wait(smem_u32(&bar_stats[j]), 0u);
            if (lane == 0) {
                const float* sc = s_scratch + j * (STATS_WARPS * 4);
                Stat a = {sc[0], sc[1], sc[2]};
#pragma unroll
                for (int w = 1; w < STATS_WARPS; w++) {
                    Stat o = {sc[w * 4 + 0], sc[w * 4 + 1], sc[w * 4 + 2]};
                    a = merge(a, o);
                }
                ulonglong2 pv;
                pv.x = tag_hi | (unsigned long long)__float_as_uint(a.mean);
                pv.y = tag_hi | (unsigned long long)__float_as_uint(a.m2);
                st_relaxed_v2(&g_part[j][cta], pv);
            }
            Stat acc;
            unsigned it = 0;
            while (true) {
                acc.n = 0.f; acc.mean = 0.f; acc.m2 = 0.f;
                bool ok = true;
                for (int c = lane; c < ncta; c += 32) {
                    const ulonglong2 pv = ld_relaxed_v2(&g_part[j][c]);
                    ok = ok && ((pv.x & 0xffffffff00000000ull) == tag_hi) &&
                         ((pv.y & 0xffffffff00000000ull) == tag_hi);
                    Stat o;
                    o.n = (float)((base + (c < rem ? 1 : 0)) * (UNIT_BYTES / 2));
                    o.mean = __uint_as_float((unsigned)pv.x);
                    o.m2 = __uint_as_float((unsigned)pv.y);
                    acc = merge(acc, o);
                }
                if (__all_sync(0xffffffffu, ok)) break;
                if (++it > SPIN_LIMIT) break;
                __nanosleep(100);
            }
            acc = warp_merge(acc);
            if (lane == 0) {
                const float var = acc.m2 / acc.n;
                const float rstd = 1.0f / sqrtf(var + 1e-5f);
                s_stat[j] = make_float2(acc.mean, rstd);
                mbar_arrive(smem_u32(&bar_ready[j]));
            }
        }
        __syncwarp();
        if (lane == 0) {
            const unsigned prev = atomicAdd(&g_done, 1u);
            if (prev == (unsigned)(ncta * GATHER_WARPS - 1)) {
                g_done = 0u;
                g_epoch = (unsigned)(tag);
                __threadfence();
            }
        }
    } else if (warp <= GATHER_WARPS + STATS_WARPS) {
        const int sw = warp - 1 - GATHER_WARPS;
        const int t = sw * 32 + lane;
        int s = 0;
        uint32_t ph = 0;
        for (int i = 0; i < G; i++) {
            mbar_wait(smem_u32(&bar_full[s]), ph);
            const uint4* sv = reinterpret_cast<const uint4*>(smem + (size_t)s * slot_bytes);
            float piv = 0.f, s1 = 0.f, s2 = 0.f;
            int cnt = 0;
            for (int v = t; v < nvec; v += STATS_THREADS) {
                const uint4 q = sv[v];
                if (cnt == 0) piv = bf_lo(q.x);
                const uint32_t w4[4] = {q.x, q.y, q.z, q.w};
#pragma unroll
                for (int e = 0; e < 4; e++) {
                    const float d0 = bf_lo(w4[e]) - piv;
                    const float d1 = bf_hi(w4[e]) - piv;
                    s1 += d0;
                    s2 = fmaf(d0, d0, s2);
                    s1 += d1;
                    s2 = fmaf(d1, d1, s2);
                }
                cnt += 8;
            }
            Stat st;
            st.n = (float)cnt;
            const float inv = cnt > 0 ? __fdividef(1.f, (float)cnt) : 0.f;
            const float dm = s1 * inv;
            st.mean = piv + dm;
            st.m2 = fmaxf(s2 - s1 * dm, 0.f);
            st = warp_merge(st);
            if (lane == 0) {
                float* sc = s_scratch + (i * STATS_WARPS + sw) * 4;
                sc[0] = st.n;
                sc[1] = st.mean;
                sc[2] = st.m2;
                mbar_arrive(smem_u32(&bar_stats[i]));
            }
            if (++s == nslots) { s = 0; ph ^= 1u; }
        }
    } else {
        const int t = (warp - 1 - GATHER_WARPS - STATS_WARPS) * 32 + lane;
        int s = 0;
        uint32_t ph = 0;
        for (int j = 0; j < G; j++) {
            mbar_wait(smem_u32(&bar_ready[j]), 0u);
            mbar_wait(smem_u32(&bar_full[s]), ph);
            const float2 ms = s_stat[j];
            const long long ge0 = (long long)j * GROUP_ELEMS + (long long)my_start * (UNIT_BYTES / 2);
            const int c0 = (int)(ge0 >> HW_SHIFT);
            const int vb = (int)((((long long)(c0 + 1) << HW_SHIFT) - ge0) >> 3);
            const int c1 = (c0 + 1 < C) ? c0 + 1 : c0;
            const float a0 = ms.y * s_gamma[c0];
            const float d0 = fmaf(-ms.x, a0, s_beta[c0]);
            const float a1 = ms.y * s_gamma[c1];
            const float d1 = fmaf(-ms.x, a1, s_beta[c1]);
            const uint4* sv = reinterpret_cast<const uint4*>(smem + (size_t)s * slot_bytes);
            uint4* dst = reinterpret_cast<uint4*>(out + ge0);
#pragma unroll 4
            for (int v = t; v < nvec; v += NORM_THREADS) {
                const uint4 q = sv[v];
                const float a = (v < vb) ? a0 : a1;
                const float d = (v < vb) ? d0 : d1;
                uint4 r;
                r.x = pack_bf16(fmaf(bf_lo(q.x), a, d), fmaf(bf_hi(q.x), a, d));
                r.y = pack_bf16(fmaf(bf_lo(q.y), a, d), fmaf(bf_hi(q.y), a, d));
                r.z = pack_bf16(fmaf(bf_lo(q.z), a, d), fmaf(bf_hi(q.z), a, d));
                r.w = pack_bf16(fmaf(bf_lo(q.w), a, d), fmaf(bf_hi(q.w), a, d));
                dst[v] = r;
            }
            __syncwarp();
            if (lane == 0) mbar_arrive(smem_u32(&bar_empty[s]));
            if (++s == nslots) { s = 0; ph ^= 1u; }
        }
    }
}

}

extern "C" void kernel_launch(void* const* d_in, const int* in_sizes, int n_in, void* d_out,
                              int out_size) {
    (void)in_sizes; (void)n_in; (void)out_size;
    static int num_sms = 0;
    static int nslots = 0, slot_bytes = 0, smem_bytes = 0;
    if (num_sms == 0) {
        int dev = 0, max_smem = 0;
        cudaGetDevice(&dev);
        cudaDeviceGetAttribute(&num_sms, cudaDevAttrMultiProcessorCount, dev);
        cudaDeviceGetAttribute(&max_smem, cudaDevAttrMaxSharedMemoryPerBlockOptin, dev);
        if (num_sms > gn::MAX_CTAS) num_sms = gn::MAX_CTAS;
        const int max_units = (gn::GROUP_UNITS + num_sms - 1) / num_sms;
        slot_bytes = max_units * gn::UNIT_BYTES;
        const int tail_bytes = (2 * gn::MAX_SLOTS + 2 * gn::G) * 8 + gn::G * 8 + 2 * gn::C * 4 +
                               gn::G * gn::STATS_WARPS * 4 * 4 + 64;
        nslots = (max_smem - tail_bytes) / slot_bytes;
        if (nslots > gn::MAX_SLOTS) nslots = gn::MAX_SLOTS;
        smem_bytes = nslots * slot_bytes + tail_bytes;
        cudaFuncSetAttribute(gn::gn_kernel, cudaFuncAttributeMaxDynamicSharedMemorySize, smem_bytes);
    }
    const __nv_bfloat16* x = (const __nv_bfloat16*)d_in[0];
    const __nv_bfloat16* g = (const __nv_bfloat16*)d_in[1];
    const __nv_bfloat16* b = (const __nv_bfloat16*)d_in[2];
    __nv_bfloat16* out = (__nv_bfloat16*)d_out;
    gn::gn_kernel<<<num_sms, gn::NTHREADS, smem_bytes>>>(x, g, b, out, nslots, slot_bytes);
}
```

```cpp
#include <cuda_runtime.h>
#include <cuda_bf16.h>
#include <stdint.h>

namespace gn {

constexpr int G = 32;
constexpr int C = 448;
constexpr int CPG = C / G;
constexpr int HW = 16 * 4096;
constexpr int HW_SHIFT = 16;
constexpr long long GROUP_ELEMS = (long long)CPG * HW;
constexpr int UNIT_BYTES = 128;
constexpr int GROUP_UNITS = (int)(GROUP_ELEMS * 2 / UNIT_BYTES);
constexpr int MAX_CTAS = 512;
constexpr int MAX_SLOTS = 16;
constexpr int MAX_POLL_CTAS = 160;
#define GN_POLL_SLEEP 0

#define GN_GATHER 4
constexpr int GATHER_WARPS = GN_GATHER;
constexpr int STATS_WARPS = 4;
constexpr int NORM_WARPS = 8;
constexpr int NUM_WARPS = 2 + GATHER_WARPS + STATS_WARPS + NORM_WARPS;
constexpr int NTHREADS = NUM_WARPS * 32;
constexpr int STATS_THREADS = STATS_WARPS * 32;
constexpr int NORM_THREADS = NORM_WARPS * 32;
#define GN_INFLIGHT 4
constexpr int INFLIGHT = GN_INFLIGHT;
#define GN_INFLIGHT_LO 2
#define GN_LEAD_HI 8
constexpr int INFLIGHT_LO = GN_INFLIGHT_LO;
constexpr int LEAD_HI = GN_LEAD_HI;
constexpr unsigned long long WAIT_LIMIT_NS = 20000000ull;

__device__ ulonglong2 g_part[G][MAX_CTAS];
__device__ unsigned int g_epoch;
__device__ unsigned int g_done;
#define TRACE(k, j)

__device__ __forceinline__ uint32_t smem_u32(const void* p) {
    return (uint32_t)__cvta_generic_to_shared(p);
}
__device__ __forceinline__ void mbar_init(uint32_t bar, uint32_t count) {
    asm volatile("mbarrier.init.shared::cta.b64 [%0], %1;" ::"r"(bar), "r"(count) : "memory");
}
__device__ __forceinline__ void mbar_arrive_expect_tx(uint32_t bar, uint32_t bytes) {
    asm volatile("mbarrier.arrive.expect_tx.shared::cta.b64 _, [%0], %1;" ::"r"(bar), "r"(bytes)
                 : "memory");
}
__device__ __forceinline__ void mbar_arrive(uint32_t bar) {
    asm volatile("mbarrier.arrive.shared::cta.b64 _, [%0];" ::"r"(bar) : "memory");
}
__device__ __forceinline__ bool mbar_try_wait(uint32_t bar, uint32_t parity) {
    uint32_t ok;
    asm volatile(
        "{\n\t.reg .pred p;\n\t"
        "mbarrier.try_wait.parity.shared::cta.b64 p, [%1], %2;\n\t"
        "selp.u32 %0, 1, 0, p;\n\t}"
        : "=r"(ok)
        : "r"(bar), "r"(parity)
        : "memory");
    return ok != 0;
}
__device__ __forceinline__ unsigned long long global_ns() {
    unsigned long long t;
    asm volatile("mov.u64 %0, %globaltimer;" : "=l"(t));
    return t;
}
__device__ __forceinline__ void mbar_wait(uint32_t bar, uint32_t parity) {
    if (mbar_try_wait(bar, parity)) return;
    const unsigned long long t0 = global_ns();
    while (!mbar_try_wait(bar, parity)) {
        if (global_ns() - t0 > WAIT_LIMIT_NS) break;
    }
}
__device__ __forceinline__ ulonglong2 ld_relaxed_v2(const ulonglong2* p) {
    ulonglong2 v;
    asm volatile("ld.relaxed.gpu.global.v2.b64 {%0, %1}, [%2];" : "=l"(v.x), "=l"(v.y) : "l"(p) : "memory");
    return v;
}
__device__ __forceinline__ void st_relaxed_v2(ulonglong2* p, ulonglong2 v) {
    asm volatile("st.relaxed.gpu.global.v2.b64 [%0], {%1, %2};" ::"l"(p), "l"(v.x), "l"(v.y) : "memory");
}
__device__ __forceinline__ void bulk_load(uint32_t dst, const void* src, uint32_t bytes, uint32_t bar,
                                          uint64_t policy) {
    asm volatile(
        "cp.async.bulk.shared::cluster.global.mbarrier::complete_tx::bytes.L2::cache_hint "
        "[%0], [%1], %2, [%3], %4;" ::"r"(dst), "l"(src), "r"(bytes), "r"(bar), "l"(policy)
        : "memory");
}

struct Stat {
    float n, mean, m2;
};
__device__ __forceinline__ Stat merge(const Stat a, const Stat b) {
    Stat r;
    r.n = a.n + b.n;
    const float w = (r.n > 0.f) ? __fdividef(b.n, r.n) : 0.f;
    const float d = b.mean - a.mean;
    r.mean = fmaf(d, w, a.mean);
    r.m2 = a.m2 + b.m2 + d * d * a.n * w;
    return r;
}
__device__ __forceinline__ Stat warp_merge(Stat s) {
#pragma unroll
    for (int off = 16; off >= 1; off >>= 1) {
        Stat o;
        o.n = __shfl_xor_sync(0xffffffffu, s.n, off);
        o.mean = __shfl_xor_sync(0xffffffffu, s.mean, off);
        o.m2 = __shfl_xor_sync(0xffffffffu, s.m2, off);
        s = merge(s, o);
    }
    return s;
}

__device__ __forceinline__ float bf_lo(uint32_t u) { return __uint_as_float(u << 16); }
__device__ __forceinline__ float bf_hi(uint32_t u) { return __uint_as_float(u & 0xffff0000u); }
__device__ __forceinline__ uint32_t pack_bf16(float lo, float hi) {
    uint32_t r;
    asm("cvt.rn.bf16x2.f32 %0, %1, %2;" : "=r"(r) : "f"(hi), "f"(lo));
    return r;
}

__global__ void __launch_bounds__(NTHREADS, 1)
gn_kernel(const __nv_bfloat16* __restrict__ x, const __nv_bfloat16* __restrict__ gamma,
          const __nv_bfloat16* __restrict__ beta, __nv_bfloat16* __restrict__ out, int nslots,
          int slot_bytes) {
    extern __shared__ __align__(1024) unsigned char smem[];
    unsigned char* tail = smem + (size_t)nslots * slot_bytes;
    uint64_t* bar_full = reinterpret_cast<uint64_t*>(tail);
    uint64_t* bar_empty = bar_full + MAX_SLOTS;
    uint64_t* bar_ready = bar_empty + MAX_SLOTS;
    uint64_t* bar_stats = bar_ready + G;
    float2* s_stat = reinterpret_cast<float2*>(bar_stats + G);
    float* s_gamma = reinterpret_cast<float*>(s_stat + G);
    float* s_beta = s_gamma + C;
    float* s_scratch = s_beta + C;
    int* s_norm_count = reinterpret_cast<int*>(s_scratch + G * STATS_WARPS * 4);

    const int tid = threadIdx.x;
    const int warp = tid >> 5;
    const int lane = tid & 31;
    const int cta = blockIdx.x;
    const int ncta = gridDim.x;

    const int base = GROUP_UNITS / ncta;
    const int rem = GROUP_UNITS - base * ncta;
    const int my_units = base + (cta < rem ? 1 : 0);
    const int my_start = cta * base + (cta < rem ? cta : rem);
    const uint32_t my_bytes = (uint32_t)my_units * UNIT_BYTES;
    const int nvec = my_units * (UNIT_BYTES / 16);

    if (tid == 0) {
        TRACE(3, 0);
        *s_norm_count = 0;
    }
    if (tid < nslots) {
        mbar_init(smem_u32(&bar_full[tid]), 1);
        mbar_init(smem_u32(&bar_empty[tid]), NORM_WARPS);
    } else if (tid >= 32 && tid < 32 + G) {
        mbar_init(smem_u32(&bar_ready[tid - 32]), 1);
        mbar_init(smem_u32(&bar_stats[tid - 32]), STATS_WARPS);
    }
    if (tid < 64) {
        asm volatile("fence.mbarrier_init.release.cluster;" ::: "memory");
        asm volatile("fence.proxy.async;" ::: "memory");
    }
    __syncthreads();

    if (warp == 0) {
        if (lane == 0) {
            uint64_t policy;
            asm volatile("createpolicy.fractional.L2::evict_first.b64 %0, 1.0;" : "=l"(policy));
            int s = 0;
            uint32_t ph = 0;
            int sd = 0;
            uint32_t phd = 0;
            for (int i = 0; i < G; i++) {
                if (i >= nslots) mbar_wait(smem_u32(&bar_empty[s]), ph ^ 1u);
                if (i >= INFLIGHT) {
                    mbar_wait(smem_u32(&bar_full[sd]), phd);
                    if (++sd == nslots) { sd = 0; phd ^= 1u; }
                }
                mbar_arrive_expect_tx(smem_u32(&bar_full[s]), my_bytes);
                const unsigned char* src = reinterpret_cast<const unsigned char*>(x) +
                                           (size_t)i * (GROUP_ELEMS * 2) + (size_t)my_start * UNIT_BYTES;
                bulk_load(smem_u32(smem + (size_t)s * slot_bytes), src, my_bytes,
                          smem_u32(&bar_full[s]), policy);
                if (++s == nslots) { s = 0; ph ^= 1u; }
            }
        }
    } else if (warp == 1) {
        if (lane == 0) {
            const unsigned long long tag_hi =
                ((unsigned long long)(*(volatile unsigned int*)&g_epoch) + 1ull) << 32;
            for (int j = 0; j < G; j++) {
                mbar_wait(smem_u32(&bar_stats[j]), 0u);
                const float* sc = s_scratch + j * (STATS_WARPS * 4);
                Stat a = {sc[0], sc[1], sc[2]};
#pragma unroll
                for (int w = 1; w < STATS_WARPS; w++) {
                    Stat o = {sc[w * 4 + 0], sc[w * 4 + 1], sc[w * 4 + 2]};
                    a = merge(a, o);
                }
                ulonglong2 pv;
                pv.x = tag_hi | (unsigned long long)__float_as_uint(a.mean);
                pv.y = tag_hi | (unsigned long long)__float_as_uint(a.m2);
                st_relaxed_v2(&g_part[j][cta], pv);
            }
        }
    } else if (warp < 2 + GATHER_WARPS) {
        const int k = warp - 2;
        const unsigned long long tag = (unsigned long long)(*(volatile unsigned int*)&g_epoch) + 1ull;
        const unsigned long long tag_hi = tag << 32;
        for (int j = k; j < G; j += GATHER_WARPS) {
            mbar_wait(smem_u32(&bar_stats[j]), 0u);
            constexpr int PER_LANE = (MAX_POLL_CTAS + 31) / 32;
            ulonglong2 pv[PER_LANE];
            const unsigned long long tw0 = global_ns();
            while (true) {
                bool ok = true;
#pragma unroll
                for (int m = 0; m < PER_LANE; m++) {
                    const int c = lane + 32 * m;
                    if (c < ncta) pv[m] = ld_relaxed_v2(&g_part[j][c]);
                }
#pragma unroll
                for (int m = 0; m < PER_LANE; m++) {
                    const int c = lane + 32 * m;
                    if (c < ncta)
                        ok = ok && (((pv[m].x ^ tag_hi) | (pv[m].y ^ tag_hi)) >> 32) == 0ull;
                }
                if (__all_sync(0xffffffffu, ok)) break;
                if (global_ns() - tw0 > WAIT_LIMIT_NS) break;
            }
            float sn = 0.f, sm = 0.f;
#pragma unroll
            for (int m = 0; m < PER_LANE; m++) {
                const int c = lane + 32 * m;
                if (c < ncta) {
                    const float n = (float)((base + (c < rem ? 1 : 0)) * (UNIT_BYTES / 2));
                    sn += n;
                    sm = fmaf(n, __uint_as_float((unsigned)pv[m].x), sm);
                }
            }
#pragma unroll
            for (int off = 16; off >= 1; off >>= 1) {
                sn += __shfl_xor_sync(0xffffffffu, sn, off);
                sm += __shfl_xor_sync(0xffffffffu, sm, off);
            }
            const float gmean = sm / sn;
            float sq = 0.f;
#pragma unroll
            for (int m = 0; m < PER_LANE; m++) {
                const int c = lane + 32 * m;
                if (c < ncta) {
                    const float n = (float)((base + (c < rem ? 1 : 0)) * (UNIT_BYTES / 2));
                    const float d = __uint_as_float((unsigned)pv[m].x) - gmean;
                    sq += fmaf(n * d, d, __uint_as_float((unsigned)pv[m].y));
                }
            }
#pragma unroll
            for (int off = 16; off >= 1; off >>= 1) sq += __shfl_xor_sync(0xffffffffu, sq, off);
            Stat acc;
            acc.n = sn; acc.mean = gmean; acc.m2 = sq;
            if (lane == 0) {
                const float var = acc.m2 / acc.n;
                const float rstd = 1.0f / sqrtf(var + 1e-5f);
                s_stat[j] = make_float2(acc.mean, rstd);
                TRACE(1, j);
                mbar_arrive(smem_u32(&bar_ready[j]));
            }
        }
        __syncwarp();
        if (lane == 0) {
            const unsigned prev = atomicAdd(&g_done, 1u);
            if (prev == (unsigned)(ncta * GATHER_WARPS - 1)) {
                g_done = 0u;
                g_epoch = (unsigned)(tag);
                __threadfence();
            }
        }
    } else if (warp < 2 + GATHER_WARPS + STATS_WARPS) {
        const int sw = warp - 2 - GATHER_WARPS;
        const int t = sw * 32 + lane;
        int s = 0;
        uint32_t ph = 0;
        for (int i = 0; i < G; i++) {
            mbar_wait(smem_u32(&bar_full[s]), ph);
            const uint4* sv = reinterpret_cast<const uint4*>(smem + (size_t)s * slot_bytes);
            float piv = 0.f, s1 = 0.f, s2 = 0.f;
            int cnt = 0;
            for (int v = t; v < nvec; v += STATS_THREADS) {
                const uint4 q = sv[v];
                if (cnt == 0) piv = bf_lo(q.x);
                const uint32_t w4[4] = {q.x, q.y, q.z, q.w};
#pragma unroll
                for (int e = 0; e < 4; e++) {
                    const float d0 = bf_lo(w4[e]) - piv;
                    const float d1 = bf_hi(w4[e]) - piv;
                    s1 += d0;
                    s2 = fmaf(d0, d0, s2);
                    s1 += d1;
                    s2 = fmaf(d1, d1, s2);
                }
                cnt += 8;
            }
            Stat st;
            st.n = (float)cnt;
            const float inv = cnt > 0 ? __fdividef(1.f, (float)cnt) : 0.f;
            const float dm = s1 * inv;
            st.mean = piv + dm;
            st.m2 = fmaxf(s2 - s1 * dm, 0.f);
            st = warp_merge(st);
            if (lane == 0) {
                float* sc = s_scratch + (i * STATS_WARPS + sw) * 4;
                sc[0] = st.n;
                sc[1] = st.mean;
                sc[2] = st.m2;
                mbar_arrive(smem_u32(&bar_stats[i]));
                if (sw == 0) TRACE(0, i);
            }
            if (++s == nslots) { s = 0; ph ^= 1u; }
        }
    } else {
        const int t = (warp - 2 - GATHER_WARPS - STATS_WARPS) * 32 + lane;
        for (int c = t; c < C; c += NORM_THREADS) {
            s_gamma[c] = __bfloat162float(gamma[c]);
            s_beta[c] = __bfloat162float(beta[c]);
        }
        asm volatile("bar.sync 2, %0;" ::"n"(NORM_THREADS) : "memory");
        int s = 0;
        uint32_t ph = 0;
        for (int j = 0; j < G; j++) {
            mbar_wait(smem_u32(&bar_ready[j]), 0u);
            mbar_wait(smem_u32(&bar_full[s]), ph);
            const float2 ms = s_stat[j];
            const long long ge0 = (long long)j * GROUP_ELEMS + (long long)my_start * (UNIT_BYTES / 2);
            const int c0 = (int)(ge0 >> HW_SHIFT);
            const int vb = (int)((((long long)(c0 + 1) << HW_SHIFT) - ge0) >> 3);
            const int c1 = (c0 + 1 < C) ? c0 + 1 : c0;
            const float a0 = ms.y * s_gamma[c0];
            const float d0 = fmaf(-ms.x, a0, s_beta[c0]);
            const float a1 = ms.y * s_gamma[c1];
            const float d1 = fmaf(-ms.x, a1, s_beta[c1]);
            const uint4* sv = reinterpret_cast<const uint4*>(smem + (size_t)s * slot_bytes);
            uint4* dst = reinterpret_cast<uint4*>(out + ge0);
#pragma unroll 4
            for (int v = t; v < nvec; v += NORM_THREADS) {
                const uint4 q = sv[v];
                const float a = (v < vb) ? a0 : a1;
                const float d = (v < vb) ? d0 : d1;
                uint4 r;
                r.x = pack_bf16(fmaf(bf_lo(q.x), a, d), fmaf(bf_hi(q.x), a, d));
                r.y = pack_bf16(fmaf(bf_lo(q.y), a, d), fmaf(bf_hi(q.y), a, d));
                r.z = pack_bf16(fmaf(bf_lo(q.z), a, d), fmaf(bf_hi(q.z), a, d));
                r.w = pack_bf16(fmaf(bf_lo(q.w), a, d), fmaf(bf_hi(q.w), a, d));
                dst[v] = r;
            }
            __syncwarp();
            if (lane == 0) mbar_arrive(smem_u32(&bar_empty[s]));
            if (t == 0) { *(volatile int*)s_norm_count = j + 1; TRACE(2, j); }
            if (++s == nslots) { s = 0; ph ^= 1u; }
        }
    }
}

}

extern "C" void kernel_launch(void* const* d_in, const int* in_sizes, int n_in, void* d_out,
                              int out_size) {
    (void)in_sizes; (void)n_in; (void)out_size;
    static int num_sms = 0;
    static int nslots = 0, slot_bytes = 0, smem_bytes = 0;
    if (num_sms == 0) {
        int dev = 0, max_smem = 0;
        cudaGetDevice(&dev);
        cudaDeviceGetAttribute(&num_sms, cudaDevAttrMultiProcessorCount, dev);
        cudaDeviceGetAttribute(&max_smem, cudaDevAttrMaxSharedMemoryPerBlockOptin, dev);
        if (num_sms > gn::MAX_POLL_CTAS) num_sms = gn::MAX_POLL_CTAS;
        const int max_units = (gn::GROUP_UNITS + num_sms - 1) / num_sms;
        slot_bytes = max_units * gn::UNIT_BYTES;
        const int tail_bytes = (2 * gn::MAX_SLOTS + 2 * gn::G) * 8 + gn::G * 8 + 2 * gn::C * 4 +
                               gn::G * gn::STATS_WARPS * 4 * 4 + 64;
        nslots = (max_smem - tail_bytes) / slot_bytes;
        if (nslots > gn::MAX_SLOTS) nslots = gn::MAX_SLOTS;
        smem_bytes = nslots * slot_bytes + tail_bytes;
        cudaFuncSetAttribute(gn::gn_kernel, cudaFuncAttributeMaxDynamicSharedMemorySize, smem_bytes);
    }
    const __nv_bfloat16* x = (const __nv_bfloat16*)d_in[0];
    const __nv_bfloat16* g = (const __nv_bfloat16*)d_in[1];
    const __nv_bfloat16* b = (const __nv_bfloat16*)d_in[2];
    __nv_bfloat16* out = (__nv_bfloat16*)d_out;
    gn::gn_kernel<<<num_sms, gn::NTHREADS, smem_bytes>>>(x, g, b, out, nslots, slot_bytes);
}
```

```cpp
#include <cuda_runtime.h>
#include <cuda_bf16.h>
#include <stdint.h>

namespace gn {

constexpr int G = 32;
constexpr int C = 448;
constexpr int CPG = C / G;
constexpr int HW = 16 * 4096;
constexpr int HW_SHIFT = 16;
constexpr long long GROUP_ELEMS = (long long)CPG * HW;
constexpr int UNIT_BYTES = 128;
constexpr int GROUP_UNITS = (int)(GROUP_ELEMS * 2 / UNIT_BYTES);
constexpr int MAX_CTAS = 512;
constexpr int MAX_SLOTS = 16;
constexpr int MAX_POLL_CTAS = 160;
#define GN_POLL_SLEEP 0

#define GN_GATHER 4
constexpr int GATHER_WARPS = GN_GATHER;
constexpr int STATS_WARPS = 4;
constexpr int NORM_WARPS = 8;
constexpr int NUM_WARPS = 2 + GATHER_WARPS + STATS_WARPS + NORM_WARPS;
constexpr int NTHREADS = NUM_WARPS * 32;
constexpr int STATS_THREADS = STATS_WARPS * 32;
constexpr int NORM_THREADS = NORM_WARPS * 32;
#define GN_INFLIGHT 4
constexpr int INFLIGHT = GN_INFLIGHT;
#define GN_INFLIGHT_LO 2
#define GN_LEAD_HI 8
constexpr int INFLIGHT_LO = GN_INFLIGHT_LO;
constexpr int LEAD_HI = GN_LEAD_HI;
constexpr unsigned long long WAIT_LIMIT_NS = 20000000ull;

__device__ ulonglong2 g_part[G][MAX_CTAS];
__device__ unsigned int g_epoch;
__device__ unsigned int g_done;
#define TRACE(k, j)

__device__ __forceinline__ uint32_t smem_u32(const void* p) {
    return (uint32_t)__cvta_generic_to_shared(p);
}
__device__ __forceinline__ void mbar_init(uint32_t bar, uint32_t count) {
    asm volatile("mbarrier.init.shared::cta.b64 [%0], %1;" ::"r"(bar), "r"(count) : "memory");
}
__device__ __forceinline__ void mbar_arrive_expect_tx(uint32_t bar, uint32_t bytes) {
    asm volatile("mbarrier.arrive.expect_tx.shared::cta.b64 _, [%0], %1;" ::"r"(bar), "r"(bytes)
                 : "memory");
}
__device__ __forceinline__ void mbar_arrive(uint32_t bar) {
    asm volatile("mbarrier.arrive.shared::cta.b64 _, [%0];" ::"r"(bar) : "memory");
}
__device__ __forceinline__ bool mbar_try_wait(uint32_t bar, uint32_t parity) {
    uint32_t ok;
    asm volatile(
        "{\n\t.reg .pred p;\n\t"
        "mbarrier.try_wait.parity.shared::cta.b64 p, [%1], %2;\n\t"
        "selp.u32 %0, 1, 0, p;\n\t}"
        : "=r"(ok)
        : "r"(bar), "r"(parity)
        : "memory");
    return ok != 0;
}
__device__ __forceinline__ unsigned long long global_ns() {
    unsigned long long t;
    asm volatile("mov.u64 %0, %globaltimer;" : "=l"(t));
    return t;
}
__device__ __forceinline__ void mbar_wait(uint32_t bar, uint32_t parity) {
    if (mbar_try_wait(bar, parity)) return;
    const unsigned long long t0 = global_ns();
    while (!mbar_try_wait(bar, parity)) {
        if (global_ns() - t0 > WAIT_LIMIT_NS) break;
    }
}
__device__ __forceinline__ ulonglong2 ld_relaxed_v2(const ulonglong2* p) {
    ulonglong2 v;
    asm volatile("ld.relaxed.gpu.global.v2.b64 {%0, %1}, [%2];" : "=l"(v.x), "=l"(v.y) : "l"(p) : "memory");
    return v;
}
__device__ __forceinline__ void st_relaxed_v2(ulonglong2* p, ulonglong2 v) {
    asm volatile("st.relaxed.gpu.global.v2.b64 [%0], {%1, %2};" ::"l"(p), "l"(v.x), "l"(v.y) : "memory");
}
__device__ __forceinline__ void bulk_load(uint32_t dst, const void* src, uint32_t bytes, uint32_t bar,
                                          uint64_t policy) {
    asm volatile(
        "cp.async.bulk.shared::cluster.global.mbarrier::complete_tx::bytes.L2::cache_hint "
        "[%0], [%1], %2, [%3], %4;" ::"r"(dst), "l"(src), "r"(bytes), "r"(bar), "l"(policy)
        : "memory");
}

struct Stat {
    float n, mean, m2;
};
__device__ __forceinline__ Stat merge(const Stat a, const Stat b) {
    Stat r;
    r.n = a.n + b.n;
    const float w = (r.n > 0.f) ? __fdividef(b.n, r.n) : 0.f;
    const float d = b.mean - a.mean;
    r.mean = fmaf(d, w, a.mean);
    r.m2 = a.m2 + b.m2 + d * d * a.n * w;
    return r;
}
__device__ __forceinline__ Stat warp_merge(Stat s) {
#pragma unroll
    for (int off = 16; off >= 1; off >>= 1) {
        Stat o;
        o.n = __shfl_xor_sync(0xffffffffu, s.n, off);
        o.mean = __shfl_xor_sync(0xffffffffu, s.mean, off);
        o.m2 = __shfl_xor_sync(0xffffffffu, s.m2, off);
        s = merge(s, o);
    }
    return s;
}

__device__ __forceinline__ float bf_lo(uint32_t u) { return __uint_as_float(u << 16); }
__device__ __forceinline__ float bf_hi(uint32_t u) { return __uint_as_float(u & 0xffff0000u); }
__device__ __forceinline__ uint32_t pack_bf16(float lo, float hi) {
    uint32_t r;
    asm("cvt.rn.bf16x2.f32 %0, %1, %2;" : "=r"(r) : "f"(hi), "f"(lo));
    return r;
}

__global__ void __launch_bounds__(NTHREADS, 1)
gn_kernel(const __nv_bfloat16* __restrict__ x, const __nv_bfloat16* __restrict__ gamma,
          const __nv_bfloat16* __restrict__ beta, __nv_bfloat16* __restrict__ out, int nslots,
          int slot_bytes) {
    extern __shared__ __align__(1024) unsigned char smem[];
    unsigned char* tail = smem + (size_t)nslots * slot_bytes;
    uint64_t* bar_full = reinterpret_cast<uint64_t*>(tail);
    uint64_t* bar_empty = bar_full + MAX_SLOTS;
    uint64_t* bar_ready = bar_empty + MAX_SLOTS;
    uint64_t* bar_stats = bar_ready + G;
    float2* s_stat = reinterpret_cast<float2*>(bar_stats + G);
    float* s_gamma = reinterpret_cast<float*>(s_stat + G);
    float* s_beta = s_gamma + C;
    float* s_scratch = s_beta + C;
    int* s_norm_count = reinterpret_cast<int*>(s_scratch + G * STATS_WARPS * 4);

    const int tid = threadIdx.x;
    const int warp = tid >> 5;
    const int lane = tid & 31;
    const int cta = blockIdx.x;
    const int ncta = gridDim.x;

    const int base = GROUP_UNITS / ncta;
    const int rem = GROUP_UNITS - base * ncta;
    const int my_units = base + (cta < rem ? 1 : 0);
    const int my_start = cta * base + (cta < rem ? cta : rem);
    const uint32_t my_bytes = (uint32_t)my_units * UNIT_BYTES;
    const int nvec = my_units * (UNIT_BYTES / 16);

    if (tid == 0) {
        TRACE(3, 0);
        *s_norm_count = 0;
        for (int s = 0; s < nslots; s++) {
            mbar_init(smem_u32(&bar_full[s]), 1);
            mbar_init(smem_u32(&bar_empty[s]), 1);
        }
        for (int j = 0; j < G; j++) {
            mbar_init(smem_u32(&bar_ready[j]), 1);
            mbar_init(smem_u32(&bar_stats[j]), STATS_WARPS);
        }
        asm volatile("fence.mbarrier_init.release.cluster;" ::: "memory");
        asm volatile("fence.proxy.async;" ::: "memory");
    }
    for (int c = tid; c < C; c += NTHREADS) {
        s_gamma[c] = __bfloat162float(gamma[c]);
        s_beta[c] = __bfloat162float(beta[c]);
    }
    __syncthreads();

    if (warp == 0) {
        if (lane == 0) {
            uint64_t policy;
            asm volatile("createpolicy.fractional.L2::evict_first.b64 %0, 1.0;" : "=l"(policy));
            int s = 0;
            uint32_t ph = 0;
            int sd = 0;
            uint32_t phd = 0;
            for (int i = 0; i < G; i++) {
                if (i >= nslots) mbar_wait(smem_u32(&bar_empty[s]), ph ^ 1u);
                if (i >= INFLIGHT) {
                    mbar_wait(smem_u32(&bar_full[sd]), phd);
                    if (++sd == nslots) { sd = 0; phd ^= 1u; }
                }
                mbar_arrive_expect_tx(smem_u32(&bar_full[s]), my_bytes);
                const unsigned char* src = reinterpret_cast<const unsigned char*>(x) +
                                           (size_t)i * (GROUP_ELEMS * 2) + (size_t)my_start * UNIT_BYTES;
                bulk_load(smem_u32(smem + (size_t)s * slot_bytes), src, my_bytes,
                          smem_u32(&bar_full[s]), policy);
                if (++s == nslots) { s = 0; ph ^= 1u; }
            }
        }
    } else if (warp == 1) {
        if (lane == 0) {
            const unsigned long long tag_hi =
                ((unsigned long long)(*(volatile unsigned int*)&g_epoch) + 1ull) << 32;
            for (int j = 0; j < G; j++) {
                mbar_wait(smem_u32(&bar_stats[j]), 0u);
                const float* sc = s_scratch + j * (STATS_WARPS * 4);
                Stat a = {sc[0], sc[1], sc[2]};
#pragma unroll
                for (int w = 1; w < STATS_WARPS; w++) {
                    Stat o = {sc[w * 4 + 0], sc[w * 4 + 1], sc[w * 4 + 2]};
                    a = merge(a, o);
                }
                ulonglong2 pv;
                pv.x = tag_hi | (unsigned long long)__float_as_uint(a.mean);
                pv.y = tag_hi | (unsigned long long)__float_as_uint(a.m2);
                st_relaxed_v2(&g_part[j][cta], pv);
            }
        }
    } else if (warp < 2 + GATHER_WARPS) {
        const int k = warp - 2;
        const unsigned long long tag = (unsigned long long)(*(volatile unsigned int*)&g_epoch) + 1ull;
        const unsigned long long tag_hi = tag << 32;
        for (int j = k; j < G; j += GATHER_WARPS) {
            mbar_wait(smem_u32(&bar_stats[j]), 0u);
            constexpr int PER_LANE = (MAX_POLL_CTAS + 31) / 32;
            ulonglong2 pv[PER_LANE];
            const unsigned long long tw0 = global_ns();
            while (true) {
                bool ok = true;
#pragma unroll
                for (int m = 0; m < PER_LANE; m++) {
                    const int c = lane + 32 * m;
                    if (c < ncta) pv[m] = ld_relaxed_v2(&g_part[j][c]);
                }
#pragma unroll
                for (int m = 0; m < PER_LANE; m++) {
                    const int c = lane + 32 * m;
                    if (c < ncta)
                        ok = ok && (((pv[m].x ^ tag_hi) | (pv[m].y ^ tag_hi)) >> 32) == 0ull;
                }
                if (__all_sync(0xffffffffu, ok)) break;
                if (global_ns() - tw0 > WAIT_LIMIT_NS) break;
            }
            float sn = 0.f, sm = 0.f;
#pragma unroll
            for (int m = 0; m < PER_LANE; m++) {
                const int c = lane + 32 * m;
                if (c < ncta) {
                    const float n = (float)((base + (c < rem ? 1 : 0)) * (UNIT_BYTES / 2));
                    sn += n;
                    sm = fmaf(n, __uint_as_float((unsigned)pv[m].x), sm);
                }
            }
#pragma unroll
            for (int off = 16; off >= 1; off >>= 1) {
                sn += __shfl_xor_sync(0xffffffffu, sn, off);
                sm += __shfl_xor_sync(0xffffffffu, sm, off);
            }
            const float gmean = sm / sn;
            float sq = 0.f;
#pragma unroll
            for (int m = 0; m < PER_LANE; m++) {
                const int c = lane + 32 * m;
                if (c < ncta) {
                    const float n = (float)((base + (c < rem ? 1 : 0)) * (UNIT_BYTES / 2));
                    const float d = __uint_as_float((unsigned)pv[m].x) - gmean;
                    sq += fmaf(n * d, d, __uint_as_float((unsigned)pv[m].y));
                }
            }
#pragma unroll
            for (int off = 16; off >= 1; off >>= 1) sq += __shfl_xor_sync(0xffffffffu, sq, off);
            Stat acc;
            acc.n = sn; acc.mean = gmean; acc.m2 = sq;
            if (lane == 0) {
                const float var = acc.m2 / acc.n;
                const float rstd = 1.0f / sqrtf(var + 1e-5f);
                s_stat[j] = make_float2(acc.mean, rstd);
                TRACE(1, j);
                mbar_arrive(smem_u32(&bar_ready[j]));
            }
        }
        __syncwarp();
        if (lane == 0) {
            const unsigned prev = atomicAdd(&g_done, 1u);
            if (prev == (unsigned)(ncta * GATHER_WARPS - 1)) {
                g_done = 0u;
                g_epoch = (unsigned)(tag);
                __threadfence();
            }
        }
    } else if (warp < 2 + GATHER_WARPS + STATS_WARPS) {
        const int sw = warp - 2 - GATHER_WARPS;
        const int t = sw * 32 + lane;
        int s = 0;
        uint32_t ph = 0;
        for (int i = 0; i < G; i++) {
            mbar_wait(smem_u32(&bar_full[s]), ph);
            const uint4* sv = reinterpret_cast<const uint4*>(smem + (size_t)s * slot_bytes);
            float piv = 0.f, s1 = 0.f, s2 = 0.f;
            int cnt = 0;
            for (int v = t; v < nvec; v += STATS_THREADS) {
                const uint4 q = sv[v];
                if (cnt == 0) piv = bf_lo(q.x);
                const uint32_t w4[4] = {q.x, q.y, q.z, q.w};
#pragma unroll
                for (int e = 0; e < 4; e++) {
                    const float d0 = bf_lo(w4[e]) - piv;
                    const float d1 = bf_hi(w4[e]) - piv;
                    s1 += d0;
                    s2 = fmaf(d0, d0, s2);
                    s1 += d1;
                    s2 = fmaf(d1, d1, s2);
                }
                cnt += 8;
            }
            Stat st;
            st.n = (float)cnt;
            const float inv = cnt > 0 ? __fdividef(1.f, (float)cnt) : 0.f;
            const float dm = s1 * inv;
            st.mean = piv + dm;
            st.m2 = fmaxf(s2 - s1 * dm, 0.f);
            st = warp_merge(st);
            if (lane == 0) {
                float* sc = s_scratch + (i * STATS_WARPS + sw) * 4;
                sc[0] = st.n;
                sc[1] = st.mean;
                sc[2] = st.m2;
                mbar_arrive(smem_u32(&bar_stats[i]));
                if (sw == 0) TRACE(0, i);
            }
            if (++s == nslots) { s = 0; ph ^= 1u; }
        }
    } else {
        const int t = (warp - 2 - GATHER_WARPS - STATS_WARPS) * 32 + lane;
        int s = 0, prev_s = 0;
        uint32_t ph = 0;
        for (int j = 0; j < G; j++) {
            mbar_wait(smem_u32(&bar_ready[j]), 0u);
            mbar_wait(smem_u32(&bar_full[s]), ph);
            const float2 ms = s_stat[j];
            const long long ge0 = (long long)j * GROUP_ELEMS + (long long)my_start * (UNIT_BYTES / 2);
            const int c0 = (int)(ge0 >> HW_SHIFT);
            const int vb = (int)((((long long)(c0 + 1) << HW_SHIFT) - ge0) >> 3);
            const int c1 = (c0 + 1 < C) ? c0 + 1 : c0;
            const float a0 = ms.y * s_gamma[c0];
            const float d0 = fmaf(-ms.x, a0, s_beta[c0]);
            const float a1 = ms.y * s_gamma[c1];
            const float d1 = fmaf(-ms.x, a1, s_beta[c1]);
            uint4* sv = reinterpret_cast<uint4*>(smem + (size_t)s * slot_bytes);
#pragma unroll 4
            for (int v = t; v < nvec; v += NORM_THREADS) {
                const uint4 q = sv[v];
                const float a = (v < vb) ? a0 : a1;
                const float d = (v < vb) ? d0 : d1;
                uint4 r;
                r.x = pack_bf16(fmaf(bf_lo(q.x), a, d), fmaf(bf_hi(q.x), a, d));
                r.y = pack_bf16(fmaf(bf_lo(q.y), a, d), fmaf(bf_hi(q.y), a, d));
                r.z = pack_bf16(fmaf(bf_lo(q.z), a, d), fmaf(bf_hi(q.z), a, d));
                r.w = pack_bf16(fmaf(bf_lo(q.w), a, d), fmaf(bf_hi(q.w), a, d));
                sv[v] = r;
            }
            asm volatile("fence.proxy.async.shared::cta;" ::: "memory");
            asm volatile("bar.sync 2, %0;" ::"n"(NORM_THREADS) : "memory");
            if (t == 0) {
                asm volatile("cp.async.bulk.global.shared::cta.bulk_group [%0], [%1], %2;" ::"l"(out + ge0),
                             "r"(smem_u32(sv)), "r"(my_bytes) : "memory");
                asm volatile("cp.async.bulk.commit_group;" ::: "memory");
                if (j > 0) {
                    asm volatile("cp.async.bulk.wait_group.read 1;" ::: "memory");
                    mbar_arrive(smem_u32(&bar_empty[prev_s]));
                }
                if (j == G - 1) asm volatile("cp.async.bulk.wait_group 0;" ::: "memory");
                *(volatile int*)s_norm_count = j + 1; TRACE(2, j);
            }
            prev_s = s;
            if (++s == nslots) { s = 0; ph ^= 1u; }
        }
    }
}

}

extern "C" void kernel_launch(void* const* d_in, const int* in_sizes, int n_in, void* d_out,
                              int out_size) {
    (void)in_sizes; (void)n_in; (void)out_size;
    static int num_sms = 0;
    static int nslots = 0, slot_bytes = 0, smem_bytes = 0;
    if (num_sms == 0) {
        int dev = 0, max_smem = 0;
        cudaGetDevice(&dev);
        cudaDeviceGetAttribute(&num_sms, cudaDevAttrMultiProcessorCount, dev);
        cudaDeviceGetAttribute(&max_smem, cudaDevAttrMaxSharedMemoryPerBlockOptin, dev);
        if (num_sms > gn::MAX_POLL_CTAS) num_sms = gn::MAX_POLL_CTAS;
        const int max_units = (gn::GROUP_UNITS + num_sms - 1) / num_sms;
        slot_bytes = max_units * gn::UNIT_BYTES;
        const int tail_bytes = (2 * gn::MAX_SLOTS + 2 * gn::G) * 8 + gn::G * 8 + 2 * gn::C * 4 +
                               gn::G * gn::STATS_WARPS * 4 * 4 + 64;
        nslots = (max_smem - tail_bytes) / slot_bytes;
        if (nslots > gn::MAX_SLOTS) nslots = gn::MAX_SLOTS;
        smem_bytes = nslots * slot_bytes + tail_bytes;
        cudaFuncSetAttribute(gn::gn_kernel, cudaFuncAttributeMaxDynamicSharedMemorySize, smem_bytes);
    }
    const __nv_bfloat16* x = (const __nv_bfloat16*)d_in[0];
    const __nv_bfloat16* g = (const __nv_bfloat16*)d_in[1];
    const __nv_bfloat16* b = (const __nv_bfloat16*)d_in[2];
    __nv_bfloat16* out = (__nv_bfloat16*)d_out;
    gn::gn_kernel<<<num_sms, gn::NTHREADS, smem_bytes>>>(x, g, b, out, nslots, slot_bytes);
}
```

```cpp
#include <cuda_runtime.h>
#include <cuda_bf16.h>
#include <stdint.h>

namespace gn {

constexpr int G = 32;
constexpr int C = 448;
constexpr int CPG = C / G;
constexpr int HW = 16 * 4096;
constexpr int HW_SHIFT = 16;
constexpr long long GROUP_ELEMS = (long long)CPG * HW;
constexpr int UNIT_BYTES = 128;
constexpr int GROUP_UNITS = (int)(GROUP_ELEMS * 2 / UNIT_BYTES);
constexpr int MAX_CTAS = 512;
constexpr int MAX_SLOTS = 16;
constexpr int MAX_POLL_CTAS = 160;
#define GN_POLL_SLEEP 0

#define GN_GATHER 4
constexpr int GATHER_WARPS = GN_GATHER;
constexpr int STATS_WARPS = 4;
constexpr int NORM_WARPS = 8;
constexpr int NUM_WARPS = 2 + GATHER_WARPS + STATS_WARPS + NORM_WARPS;
constexpr int NTHREADS = NUM_WARPS * 32;
constexpr int STATS_THREADS = STATS_WARPS * 32;
constexpr int NORM_THREADS = NORM_WARPS * 32;
#define GN_INFLIGHT 4
constexpr int INFLIGHT = GN_INFLIGHT;
#define GN_DEFER 8
constexpr int DEFER = GN_DEFER;
#define GN_INFLIGHT_LO 2
#define GN_LEAD_HI 8
constexpr int INFLIGHT_LO = GN_INFLIGHT_LO;
constexpr int LEAD_HI = GN_LEAD_HI;
constexpr unsigned long long WAIT_LIMIT_NS = 20000000ull;

__device__ ulonglong2 g_part[G][MAX_CTAS];
__device__ unsigned int g_epoch;
__device__ unsigned int g_done;
#define TRACE(k, j)

__device__ __forceinline__ uint32_t smem_u32(const void* p) {
    return (uint32_t)__cvta_generic_to_shared(p);
}
__device__ __forceinline__ void mbar_init(uint32_t bar, uint32_t count) {
    asm volatile("mbarrier.init.shared::cta.b64 [%0], %1;" ::"r"(bar), "r"(count) : "memory");
}
__device__ __forceinline__ void mbar_arrive_expect_tx(uint32_t bar, uint32_t bytes) {
    asm volatile("mbarrier.arrive.expect_tx.shared::cta.b64 _, [%0], %1;" ::"r"(bar), "r"(bytes)
                 : "memory");
}
__device__ __forceinline__ void mbar_arrive(uint32_t bar) {
    asm volatile("mbarrier.arrive.shared::cta.b64 _, [%0];" ::"r"(bar) : "memory");
}
__device__ __forceinline__ bool mbar_try_wait(uint32_t bar, uint32_t parity) {
    uint32_t ok;
    asm volatile(
        "{\n\t.reg .pred p;\n\t"
        "mbarrier.try_wait.parity.shared::cta.b64 p, [%1], %2;\n\t"
        "selp.u32 %0, 1, 0, p;\n\t}"
        : "=r"(ok)
        : "r"(bar), "r"(parity)
        : "memory");
    return ok != 0;
}
__device__ __forceinline__ unsigned long long global_ns() {
    unsigned long long t;
    asm volatile("mov.u64 %0, %globaltimer;" : "=l"(t));
    return t;
}
__device__ __forceinline__ void mbar_wait(uint32_t bar, uint32_t parity) {
    if (mbar_try_wait(bar, parity)) return;
    const unsigned long long t0 = global_ns();
    while (!mbar_try_wait(bar, parity)) {
        if (global_ns() - t0 > WAIT_LIMIT_NS) break;
    }
}
__device__ __forceinline__ ulonglong2 ld_relaxed_v2(const ulonglong2* p) {
    ulonglong2 v;
    asm volatile("ld.relaxed.gpu.global.v2.b64 {%0, %1}, [%2];" : "=l"(v.x), "=l"(v.y) : "l"(p) : "memory");
    return v;
}
__device__ __forceinline__ void st_relaxed_v2(ulonglong2* p, ulonglong2 v) {
    asm volatile("st.relaxed.gpu.global.v2.b64 [%0], {%1, %2};" ::"l"(p), "l"(v.x), "l"(v.y) : "memory");
}
__device__ __forceinline__ void bulk_load(uint32_t dst, const void* src, uint32_t bytes, uint32_t bar,
                                          uint64_t policy) {
    asm volatile(
        "cp.async.bulk.shared::cluster.global.mbarrier::complete_tx::bytes.L2::cache_hint "
        "[%0], [%1], %2, [%3], %4;" ::"r"(dst), "l"(src), "r"(bytes), "r"(bar), "l"(policy)
        : "memory");
}

struct Stat {
    float n, mean, m2;
};
__device__ __forceinline__ Stat merge(const Stat a, const Stat b) {
    Stat r;
    r.n = a.n + b.n;
    const float w = (r.n > 0.f) ? __fdividef(b.n, r.n) : 0.f;
    const float d = b.mean - a.mean;
    r.mean = fmaf(d, w, a.mean);
    r.m2 = a.m2 + b.m2 + d * d * a.n * w;
    return r;
}
__device__ __forceinline__ Stat warp_merge(Stat s) {
#pragma unroll
    for (int off = 16; off >= 1; off >>= 1) {
        Stat o;
        o.n = __shfl_xor_sync(0xffffffffu, s.n, off);
        o.mean = __shfl_xor_sync(0xffffffffu, s.mean, off);
        o.m2 = __shfl_xor_sync(0xffffffffu, s.m2, off);
        s = merge(s, o);
    }
    return s;
}

__device__ __forceinline__ float bf_lo(uint32_t u) { return __uint_as_float(u << 16); }
__device__ __forceinline__ float bf_hi(uint32_t u) { return __uint_as_float(u & 0xffff0000u); }
__device__ __forceinline__ uint32_t pack_bf16(float lo, float hi) {
    uint32_t r;
    asm("cvt.rn.bf16x2.f32 %0, %1, %2;" : "=r"(r) : "f"(hi), "f"(lo));
    return r;
}

__global__ void __launch_bounds__(NTHREADS, 1)
gn_kernel(const __nv_bfloat16* __restrict__ x, const __nv_bfloat16* __restrict__ gamma,
          const __nv_bfloat16* __restrict__ beta, __nv_bfloat16* __restrict__ out, int nslots,
          int slot_bytes) {
    extern __shared__ __align__(1024) unsigned char smem[];
    unsigned char* tail = smem + (size_t)nslots * slot_bytes;
    uint64_t* bar_full = reinterpret_cast<uint64_t*>(tail);
    uint64_t* bar_empty = bar_full + MAX_SLOTS;
    uint64_t* bar_ready = bar_empty + MAX_SLOTS;
    uint64_t* bar_stats = bar_ready + G;
    float2* s_stat = reinterpret_cast<float2*>(bar_stats + G);
    float* s_gamma = reinterpret_cast<float*>(s_stat + G);
    float* s_beta = s_gamma + C;
    float* s_scratch = s_beta + C;
    int* s_norm_count = reinterpret_cast<int*>(s_scratch + G * STATS_WARPS * 4);

    const int tid = threadIdx.x;
    const int warp = tid >> 5;
    const int lane = tid & 31;
    const int cta = blockIdx.x;
    const int ncta = gridDim.x;

    const int base = GROUP_UNITS / ncta;
    const int rem = GROUP_UNITS - base * ncta;
    const int my_units = base + (cta < rem ? 1 : 0);
    const int my_start = cta * base + (cta < rem ? cta : rem);
    const uint32_t my_bytes = (uint32_t)my_units * UNIT_BYTES;
    const int nvec = my_units * (UNIT_BYTES / 16);

    if (tid == 0) {
        TRACE(3, 0);
        *s_norm_count = 0;
        for (int s = 0; s < nslots; s++) {
            mbar_init(smem_u32(&bar_full[s]), 1);
            mbar_init(smem_u32(&bar_empty[s]), NORM_WARPS);
        }
        for (int j = 0; j < G; j++) {
            mbar_init(smem_u32(&bar_ready[j]), 1);
            mbar_init(smem_u32(&bar_stats[j]), STATS_WARPS);
        }
        asm volatile("fence.mbarrier_init.release.cluster;" ::: "memory");
        asm volatile("fence.proxy.async;" ::: "memory");
    }
    for (int c = tid; c < C; c += NTHREADS) {
        s_gamma[c] = __bfloat162float(gamma[c]);
        s_beta[c] = __bfloat162float(beta[c]);
    }
    __syncthreads();

    if (warp == 0) {
        if (lane == 0) {
            uint64_t policy;
            asm volatile("createpolicy.fractional.L2::evict_first.b64 %0, 1.0;" : "=l"(policy));
            int s = 0;
            uint32_t ph = 0;
            int sd = 0;
            uint32_t phd = 0;
            for (int i = 0; i < G; i++) {
                if (i >= nslots) mbar_wait(smem_u32(&bar_empty[s]), ph ^ 1u);
                if (i >= INFLIGHT) {
                    mbar_wait(smem_u32(&bar_full[sd]), phd);
                    if (++sd == nslots) { sd = 0; phd ^= 1u; }
                }
                mbar_arrive_expect_tx(smem_u32(&bar_full[s]), my_bytes);
                const unsigned char* src = reinterpret_cast<const unsigned char*>(x) +
                                           (size_t)i * (GROUP_ELEMS * 2) + (size_t)my_start * UNIT_BYTES;
                bulk_load(smem_u32(smem + (size_t)s * slot_bytes), src, my_bytes,
                          smem_u32(&bar_full[s]), policy);
                if (++s == nslots) { s = 0; ph ^= 1u; }
            }
        }
    } else if (warp == 1) {
        if (lane == 0) {
            const unsigned long long tag_hi =
                ((unsigned long long)(*(volatile unsigned int*)&g_epoch) + 1ull) << 32;
            for (int j = 0; j < G; j++) {
                mbar_wait(smem_u32(&bar_stats[j]), 0u);
                const float* sc = s_scratch + j * (STATS_WARPS * 4);
                Stat a = {sc[0], sc[1], sc[2]};
#pragma unroll
                for (int w = 1; w < STATS_WARPS; w++) {
                    Stat o = {sc[w * 4 + 0], sc[w * 4 + 1], sc[w * 4 + 2]};
                    a = merge(a, o);
                }
                ulonglong2 pv;
                pv.x = tag_hi | (unsigned long long)__float_as_uint(a.mean);
                pv.y = tag_hi | (unsigned long long)__float_as_uint(a.m2);
                st_relaxed_v2(&g_part[j][cta], pv);
            }
        }
    } else if (warp < 2 + GATHER_WARPS) {
        const int k = warp - 2;
        const unsigned long long tag = (unsigned long long)(*(volatile unsigned int*)&g_epoch) + 1ull;
        const unsigned long long tag_hi = tag << 32;
        for (int j = k; j < G; j += GATHER_WARPS) {
            mbar_wait(smem_u32(&bar_stats[j]), 0u);
            constexpr int PER_LANE = (MAX_POLL_CTAS + 31) / 32;
            ulonglong2 pv[PER_LANE];
            const unsigned long long tw0 = global_ns();
            while (true) {
                bool ok = true;
#pragma unroll
                for (int m = 0; m < PER_LANE; m++) {
                    const int c = lane + 32 * m;
                    if (c < ncta) pv[m] = ld_relaxed_v2(&g_part[j][c]);
                }
#pragma unroll
                for (int m = 0; m < PER_LANE; m++) {
                    const int c = lane + 32 * m;
                    if (c < ncta)
                        ok = ok && (((pv[m].x ^ tag_hi) | (pv[m].y ^ tag_hi)) >> 32) == 0ull;
                }
                if (__all_sync(0xffffffffu, ok)) break;
                if (global_ns() - tw0 > WAIT_LIMIT_NS) break;
            }
            float sn = 0.f, sm = 0.f;
#pragma unroll
            for (int m = 0; m < PER_LANE; m++) {
                const int c = lane + 32 * m;
                if (c < ncta) {
                    const float n = (float)((base + (c < rem ? 1 : 0)) * (UNIT_BYTES / 2));
                    sn += n;
                    sm = fmaf(n, __uint_as_float((unsigned)pv[m].x), sm);
                }
            }
#pragma unroll
            for (int off = 16; off >= 1; off >>= 1) {
                sn += __shfl_xor_sync(0xffffffffu, sn, off);
                sm += __shfl_xor_sync(0xffffffffu, sm, off);
            }
            const float gmean = sm / sn;
            float sq = 0.f;
#pragma unroll
            for (int m = 0; m < PER_LANE; m++) {
                const int c = lane + 32 * m;
                if (c < ncta) {
                    const float n = (float)((base + (c < rem ? 1 : 0)) * (UNIT_BYTES / 2));
                    const float d = __uint_as_float((unsigned)pv[m].x) - gmean;
                    sq += fmaf(n * d, d, __uint_as_float((unsigned)pv[m].y));
                }
            }
#pragma unroll
            for (int off = 16; off >= 1; off >>= 1) sq += __shfl_xor_sync(0xffffffffu, sq, off);
            Stat acc;
            acc.n = sn; acc.mean = gmean; acc.m2 = sq;
            if (lane == 0) {
                const float var = acc.m2 / acc.n;
                const float rstd = 1.0f / sqrtf(var + 1e-5f);
                s_stat[j] = make_float2(acc.mean, rstd);
                TRACE(1, j);
                mbar_arrive(smem_u32(&bar_ready[j]));
            }
        }
        __syncwarp();
        if (lane == 0) {
            const unsigned prev = atomicAdd(&g_done, 1u);
            if (prev == (unsigned)(ncta * GATHER_WARPS - 1)) {
                g_done = 0u;
                g_epoch = (unsigned)(tag);
                __threadfence();
            }
        }
    } else if (warp < 2 + GATHER_WARPS + STATS_WARPS) {
        const int sw = warp - 2 - GATHER_WARPS;
        const int t = sw * 32 + lane;
        int s = 0;
        uint32_t ph = 0;
        for (int i = 0; i < G; i++) {
            mbar_wait(smem_u32(&bar_full[s]), ph);
            const uint4* sv = reinterpret_cast<const uint4*>(smem + (size_t)s * slot_bytes);
            float piv = 0.f, s1 = 0.f, s2 = 0.f;
            int cnt = 0;
            for (int v = t; v < nvec; v += STATS_THREADS) {
                const uint4 q = sv[v];
                if (cnt == 0) piv = bf_lo(q.x);
                const uint32_t w4[4] = {q.x, q.y, q.z, q.w};
#pragma unroll
                for (int e = 0; e < 4; e++) {
                    const float d0 = bf_lo(w4[e]) - piv;
                    const float d1 = bf_hi(w4[e]) - piv;
                    s1 += d0;
                    s2 = fmaf(d0, d0, s2);
                    s1 += d1;
                    s2 = fmaf(d1, d1, s2);
                }
                cnt += 8;
            }
            Stat st;
            st.n = (float)cnt;
            const float inv = cnt > 0 ? __fdividef(1.f, (float)cnt) : 0.f;
            const float dm = s1 * inv;
            st.mean = piv + dm;
            st.m2 = fmaxf(s2 - s1 * dm, 0.f);
            st = warp_merge(st);
            if (lane == 0) {
                float* sc = s_scratch + (i * STATS_WARPS + sw) * 4;
                sc[0] = st.n;
                sc[1] = st.mean;
                sc[2] = st.m2;
                mbar_arrive(smem_u32(&bar_stats[i]));
                if (sw == 0) TRACE(0, i);
            }
            if (++s == nslots) { s = 0; ph ^= 1u; }
        }
    } else {
        const int t = (warp - 2 - GATHER_WARPS - STATS_WARPS) * 32 + lane;
        int s = 0;
        uint32_t ph = 0;
        for (int j = 0; j < G; j++) {
            {
                const int jd = (j + DEFER < G) ? j + DEFER : G - 1;
                mbar_wait(smem_u32(&bar_full[jd % nslots]), (uint32_t)((jd / nslots) & 1));
            }
            mbar_wait(smem_u32(&bar_ready[j]), 0u);
            mbar_wait(smem_u32(&bar_full[s]), ph);
            const float2 ms = s_stat[j];
            const long long ge0 = (long long)j * GROUP_ELEMS + (long long)my_start * (UNIT_BYTES / 2);
            const int c0 = (int)(ge0 >> HW_SHIFT);
            const int vb = (int)((((long long)(c0 + 1) << HW_SHIFT) - ge0) >> 3);
            const int c1 = (c0 + 1 < C) ? c0 + 1 : c0;
            const float a0 = ms.y * s_gamma[c0];
            const float d0 = fmaf(-ms.x, a0, s_beta[c0]);
            const float a1 = ms.y * s_gamma[c1];
            const float d1 = fmaf(-ms.x, a1, s_beta[c1]);
            const uint4* sv = reinterpret_cast<const uint4*>(smem + (size_t)s * slot_bytes);
            uint4* dst = reinterpret_cast<uint4*>(out + ge0);
#pragma unroll 4
            for (int v = t; v < nvec; v += NORM_THREADS) {
                const uint4 q = sv[v];
                const float a = (v < vb) ? a0 : a1;
                const float d = (v < vb) ? d0 : d1;
                uint4 r;
                r.x = pack_bf16(fmaf(bf_lo(q.x), a, d), fmaf(bf_hi(q.x), a, d));
                r.y = pack_bf16(fmaf(bf_lo(q.y), a, d), fmaf(bf_hi(q.y), a, d));
                r.z = pack_bf16(fmaf(bf_lo(q.z), a, d), fmaf(bf_hi(q.z), a, d));
                r.w = pack_bf16(fmaf(bf_lo(q.w), a, d), fmaf(bf_hi(q.w), a, d));
                dst[v] = r;
            }
            __syncwarp();
            if (lane == 0) mbar_arrive(smem_u32(&bar_empty[s]));
            if (t == 0) { *(volatile int*)s_norm_count = j + 1; TRACE(2, j); }
            if (++s == nslots) { s = 0; ph ^= 1u; }
        }
    }
}

}

extern "C" void kernel_launch(void* const* d_in, const int* in_sizes, int n_in, void* d_out,
                              int out_size) {
    (void)in_sizes; (void)n_in; (void)out_size;
    static int num_sms = 0;
    static int nslots = 0, slot_bytes = 0, smem_bytes = 0;
    if (num_sms == 0) {
        int dev = 0, max_smem = 0;
        cudaGetDevice(&dev);
        cudaDeviceGetAttribute(&num_sms, cudaDevAttrMultiProcessorCount, dev);
        cudaDeviceGetAttribute(&max_smem, cudaDevAttrMaxSharedMemoryPerBlockOptin, dev);
        if (num_sms > gn::MAX_POLL_CTAS) num_sms = gn::MAX_POLL_CTAS;
        const int max_units = (gn::GROUP_UNITS + num_sms - 1) / num_sms;
        slot_bytes = max_units * gn::UNIT_BYTES;
        const int tail_bytes = (2 * gn::MAX_SLOTS + 2 * gn::G) * 8 + gn::G * 8 + 2 * gn::C * 4 +
                               gn::G * gn::STATS_WARPS * 4 * 4 + 64;
        nslots = (max_smem - tail_bytes) / slot_bytes;
        if (nslots > gn::MAX_SLOTS) nslots = gn::MAX_SLOTS;
        smem_bytes = nslots * slot_bytes + tail_bytes;
        cudaFuncSetAttribute(gn::gn_kernel, cudaFuncAttributeMaxDynamicSharedMemorySize, smem_bytes);
    }
    const __nv_bfloat16* x = (const __nv_bfloat16*)d_in[0];
    const __nv_bfloat16* g = (const __nv_bfloat16*)d_in[1];
    const __nv_bfloat16* b = (const __nv_bfloat16*)d_in[2];
    __nv_bfloat16* out = (__nv_bfloat16*)d_out;
    gn::gn_kernel<<<num_sms, gn::NTHREADS, smem_bytes>>>(x, g, b, out, nslots, slot_bytes);
}
```

```cpp
#include <cuda_runtime.h>
#include <cuda_bf16.h>
#include <stdint.h>

namespace gn {

constexpr int G = 32;
constexpr int C = 448;
constexpr int CPG = C / G;
constexpr int HW = 16 * 4096;
constexpr int HW_SHIFT = 16;
constexpr long long GROUP_ELEMS = (long long)CPG * HW;
constexpr int UNIT_BYTES = 128;
constexpr int GROUP_UNITS = (int)(GROUP_ELEMS * 2 / UNIT_BYTES);
constexpr int MAX_CTAS = 512;
constexpr int MAX_SLOTS = 16;
constexpr int MAX_POLL_CTAS = 160;
#define GN_POLL_SLEEP 0

#define GN_GATHER 4
constexpr int GATHER_WARPS = GN_GATHER;
constexpr int STATS_WARPS = 4;
constexpr int NORM_WARPS = 8;
constexpr int NUM_WARPS = 2 + GATHER_WARPS + STATS_WARPS + NORM_WARPS;
constexpr int NTHREADS = NUM_WARPS * 32;
constexpr int STATS_THREADS = STATS_WARPS * 32;
constexpr int NORM_THREADS = NORM_WARPS * 32;
#define GN_INFLIGHT 4
constexpr int INFLIGHT = GN_INFLIGHT;
#define GN_INFLIGHT_LO 2
#define GN_LEAD_HI 8
constexpr int INFLIGHT_LO = GN_INFLIGHT_LO;
constexpr int LEAD_HI = GN_LEAD_HI;
constexpr unsigned long long WAIT_LIMIT_NS = 20000000ull;

__device__ ulonglong2 g_part[G][MAX_CTAS];
__device__ ulonglong2 g_final[G];
__device__ unsigned int g_epoch;
__device__ unsigned int g_done;
#define TRACE(k, j)

__device__ __forceinline__ uint32_t smem_u32(const void* p) {
    return (uint32_t)__cvta_generic_to_shared(p);
}
__device__ __forceinline__ void mbar_init(uint32_t bar, uint32_t count) {
    asm volatile("mbarrier.init.shared::cta.b64 [%0], %1;" ::"r"(bar), "r"(count) : "memory");
}
__device__ __forceinline__ void mbar_arrive_expect_tx(uint32_t bar, uint32_t bytes) {
    asm volatile("mbarrier.arrive.expect_tx.shared::cta.b64 _, [%0], %1;" ::"r"(bar), "r"(bytes)
                 : "memory");
}
__device__ __forceinline__ void mbar_arrive(uint32_t bar) {
    asm volatile("mbarrier.arrive.shared::cta.b64 _, [%0];" ::"r"(bar) : "memory");
}
__device__ __forceinline__ bool mbar_try_wait(uint32_t bar, uint32_t parity) {
    uint32_t ok;
    asm volatile(
        "{\n\t.reg .pred p;\n\t"
        "mbarrier.try_wait.parity.shared::cta.b64 p, [%1], %2;\n\t"
        "selp.u32 %0, 1, 0, p;\n\t}"
        : "=r"(ok)
        : "r"(bar), "r"(parity)
        : "memory");
    return ok != 0;
}
__device__ __forceinline__ unsigned long long global_ns() {
    unsigned long long t;
    asm volatile("mov.u64 %0, %globaltimer;" : "=l"(t));
    return t;
}
__device__ __forceinline__ void mbar_wait(uint32_t bar, uint32_t parity) {
    if (mbar_try_wait(bar, parity)) return;
    const unsigned long long t0 = global_ns();
    while (!mbar_try_wait(bar, parity)) {
        if (global_ns() - t0 > WAIT_LIMIT_NS) break;
    }
}
__device__ __forceinline__ ulonglong2 ld_relaxed_v2(const ulonglong2* p) {
    ulonglong2 v;
    asm volatile("ld.relaxed.gpu.global.v2.b64 {%0, %1}, [%2];" : "=l"(v.x), "=l"(v.y) : "l"(p) : "memory");
    return v;
}
__device__ __forceinline__ void st_relaxed_v2(ulonglong2* p, ulonglong2 v) {
    asm volatile("st.relaxed.gpu.global.v2.b64 [%0], {%1, %2};" ::"l"(p), "l"(v.x), "l"(v.y) : "memory");
}
__device__ __forceinline__ void bulk_load(uint32_t dst, const void* src, uint32_t bytes, uint32_t bar,
                                          uint64_t policy) {
    asm volatile(
        "cp.async.bulk.shared::cluster.global.mbarrier::complete_tx::bytes.L2::cache_hint "
        "[%0], [%1], %2, [%3], %4;" ::"r"(dst), "l"(src), "r"(bytes), "r"(bar), "l"(policy)
        : "memory");
}

struct Stat {
    float n, mean, m2;
};
__device__ __forceinline__ Stat merge(const Stat a, const Stat b) {
    Stat r;
    r.n = a.n + b.n;
    const float w = (r.n > 0.f) ? __fdividef(b.n, r.n) : 0.f;
    const float d = b.mean - a.mean;
    r.mean = fmaf(d, w, a.mean);
    r.m2 = a.m2 + b.m2 + d * d * a.n * w;
    return r;
}
__device__ __forceinline__ Stat warp_merge(Stat s) {
#pragma unroll
    for (int off = 16; off >= 1; off >>= 1) {
        Stat o;
        o.n = __shfl_xor_sync(0xffffffffu, s.n, off);
        o.mean = __shfl_xor_sync(0xffffffffu, s.mean, off);
        o.m2 = __shfl_xor_sync(0xffffffffu, s.m2, off);
        s = merge(s, o);
    }
    return s;
}

__device__ __forceinline__ float bf_lo(uint32_t u) { return __uint_as_float(u << 16); }
__device__ __forceinline__ float bf_hi(uint32_t u) { return __uint_as_float(u & 0xffff0000u); }
__device__ __forceinline__ uint32_t pack_bf16(float lo, float hi) {
    uint32_t r;
    asm("cvt.rn.bf16x2.f32 %0, %1, %2;" : "=r"(r) : "f"(hi), "f"(lo));
    return r;
}

__global__ void __launch_bounds__(NTHREADS, 1)
gn_kernel(const __nv_bfloat16* __restrict__ x, const __nv_bfloat16* __restrict__ gamma,
          const __nv_bfloat16* __restrict__ beta, __nv_bfloat16* __restrict__ out, int nslots,
          int slot_bytes) {
    extern __shared__ __align__(1024) unsigned char smem[];
    unsigned char* tail = smem + (size_t)nslots * slot_bytes;
    uint64_t* bar_full = reinterpret_cast<uint64_t*>(tail);
    uint64_t* bar_empty = bar_full + MAX_SLOTS;
    uint64_t* bar_ready = bar_empty + MAX_SLOTS;
    uint64_t* bar_stats = bar_ready + G;
    float2* s_stat = reinterpret_cast<float2*>(bar_stats + G);
    float* s_gamma = reinterpret_cast<float*>(s_stat + G);
    float* s_beta = s_gamma + C;
    float* s_scratch = s_beta + C;
    int* s_norm_count = reinterpret_cast<int*>(s_scratch + G * STATS_WARPS * 4);

    const int tid = threadIdx.x;
    const int warp = tid >> 5;
    const int lane = tid & 31;
    const int cta = blockIdx.x;
    const int ncta = gridDim.x;

    const int base = GROUP_UNITS / ncta;
    const int rem = GROUP_UNITS - base * ncta;
    const int my_units = base + (cta < rem ? 1 : 0);
    const int my_start = cta * base + (cta < rem ? cta : rem);
    const uint32_t my_bytes = (uint32_t)my_units * UNIT_BYTES;
    const int nvec = my_units * (UNIT_BYTES / 16);

    if (tid == 0) {
        TRACE(3, 0);
        *s_norm_count = 0;
        for (int s = 0; s < nslots; s++) {
            mbar_init(smem_u32(&bar_full[s]), 1);
            mbar_init(smem_u32(&bar_empty[s]), NORM_WARPS);
        }
        for (int j = 0; j < G; j++) {
            mbar_init(smem_u32(&bar_ready[j]), 1);
            mbar_init(smem_u32(&bar_stats[j]), STATS_WARPS);
        }
        asm volatile("fence.mbarrier_init.release.cluster;" ::: "memory");
        asm volatile("fence.proxy.async;" ::: "memory");
    }
    for (int c = tid; c < C; c += NTHREADS) {
        s_gamma[c] = __bfloat162float(gamma[c]);
        s_beta[c] = __bfloat162float(beta[c]);
    }
    __syncthreads();

    if (warp == 0) {
        if (lane == 0) {
            uint64_t policy;
            asm volatile("createpolicy.fractional.L2::evict_first.b64 %0, 1.0;" : "=l"(policy));
            int s = 0;
            uint32_t ph = 0;
            int sd = 0;
            uint32_t phd = 0;
            for (int i = 0; i < G; i++) {
                if (i >= nslots) mbar_wait(smem_u32(&bar_empty[s]), ph ^ 1u);
                if (i >= INFLIGHT) {
                    mbar_wait(smem_u32(&bar_full[sd]), phd);
                    if (++sd == nslots) { sd = 0; phd ^= 1u; }
                }
                mbar_arrive_expect_tx(smem_u32(&bar_full[s]), my_bytes);
                const unsigned char* src = reinterpret_cast<const unsigned char*>(x) +
                                           (size_t)i * (GROUP_ELEMS * 2) + (size_t)my_start * UNIT_BYTES;
                bulk_load(smem_u32(smem + (size_t)s * slot_bytes), src, my_bytes,
                          smem_u32(&bar_full[s]), policy);
                if (++s == nslots) { s = 0; ph ^= 1u; }
            }
        }
    } else if (warp == 1) {
        if (lane == 0) {
            const unsigned long long tag_hi =
                ((unsigned long long)(*(volatile unsigned int*)&g_epoch) + 1ull) << 32;
            for (int j = 0; j < G; j++) {
                mbar_wait(smem_u32(&bar_stats[j]), 0u);
                const float* sc = s_scratch + j * (STATS_WARPS * 4);
                Stat a = {sc[0], sc[1], sc[2]};
#pragma unroll
                for (int w = 1; w < STATS_WARPS; w++) {
                    Stat o = {sc[w * 4 + 0], sc[w * 4 + 1], sc[w * 4 + 2]};
                    a = merge(a, o);
                }
                ulonglong2 pv;
                pv.x = tag_hi | (unsigned long long)__float_as_uint(a.mean);
                pv.y = tag_hi | (unsigned long long)__float_as_uint(a.m2);
                st_relaxed_v2(&g_part[j][cta], pv);
            }
        }
    } else if (warp < 2 + GATHER_WARPS) {
        const int k = warp - 2;
        const unsigned long long tag = (unsigned long long)(*(volatile unsigned int*)&g_epoch) + 1ull;
        const unsigned long long tag_hi = tag << 32;
        for (int j = k; j < G; j += GATHER_WARPS) {
            mbar_wait(smem_u32(&bar_stats[j]), 0u);
            const int agg = (j * 37) % ncta;
            if (cta != agg) {
                const unsigned long long tw1 = global_ns();
                ulonglong2 fv;
                while (true) {
                    fv = ld_relaxed_v2(&g_final[j]);
                    if ((((fv.x ^ tag_hi) | (fv.y ^ tag_hi)) >> 32) == 0ull) break;
                    if (global_ns() - tw1 > WAIT_LIMIT_NS) break;
                }
                if (lane == 0) {
                    s_stat[j] = make_float2(__uint_as_float((unsigned)fv.x), __uint_as_float((unsigned)fv.y));
                    TRACE(1, j);
                    mbar_arrive(smem_u32(&bar_ready[j]));
                }
                continue;
            }
            constexpr int PER_LANE = (MAX_POLL_CTAS + 31) / 32;
            ulonglong2 pv[PER_LANE];
            const unsigned long long tw0 = global_ns();
            while (true) {
                bool ok = true;
#pragma unroll
                for (int m = 0; m < PER_LANE; m++) {
                    const int c = lane + 32 * m;
                    if (c < ncta) pv[m] = ld_relaxed_v2(&g_part[j][c]);
                }
#pragma unroll
                for (int m = 0; m < PER_LANE; m++) {
                    const int c = lane + 32 * m;
                    if (c < ncta)
                        ok = ok && (((pv[m].x ^ tag_hi) | (pv[m].y ^ tag_hi)) >> 32) == 0ull;
                }
                if (__all_sync(0xffffffffu, ok)) break;
                if (global_ns() - tw0 > WAIT_LIMIT_NS) break;
            }
            float sn = 0.f, sm = 0.f;
#pragma unroll
            for (int m = 0; m < PER_LANE; m++) {
                const int c = lane + 32 * m;
                if (c < ncta) {
                    const float n = (float)((base + (c < rem ? 1 : 0)) * (UNIT_BYTES / 2));
                    sn += n;
                    sm = fmaf(n, __uint_as_float((unsigned)pv[m].x), sm);
                }
            }
#pragma unroll
            for (int off = 16; off >= 1; off >>= 1) {
                sn += __shfl_xor_sync(0xffffffffu, sn, off);
                sm += __shfl_xor_sync(0xffffffffu, sm, off);
            }
            const float gmean = sm / sn;
            float sq = 0.f;
#pragma unroll
            for (int m = 0; m < PER_LANE; m++) {
                const int c = lane + 32 * m;
                if (c < ncta) {
                    const float n = (float)((base + (c < rem ? 1 : 0)) * (UNIT_BYTES / 2));
                    const float d = __uint_as_float((unsigned)pv[m].x) - gmean;
                    sq += fmaf(n * d, d, __uint_as_float((unsigned)pv[m].y));
                }
            }
#pragma unroll
            for (int off = 16; off >= 1; off >>= 1) sq += __shfl_xor_sync(0xffffffffu, sq, off);
            Stat acc;
            acc.n = sn; acc.mean = gmean; acc.m2 = sq;
            if (lane == 0) {
                const float var = acc.m2 / acc.n;
                const float rstd = 1.0f / sqrtf(var + 1e-5f);
                ulonglong2 fv;
                fv.x = tag_hi | (unsigned long long)__float_as_uint(acc.mean);
                fv.y = tag_hi | (unsigned long long)__float_as_uint(rstd);
                st_relaxed_v2(&g_final[j], fv);
                s_stat[j] = make_float2(acc.mean, rstd);
                TRACE(1, j);
                mbar_arrive(smem_u32(&bar_ready[j]));
            }
        }
        __syncwarp();
        if (lane == 0) {
            const unsigned prev = atomicAdd(&g_done, 1u);
            if (prev == (unsigned)(ncta * GATHER_WARPS - 1)) {
                g_done = 0u;
                g_epoch = (unsigned)(tag);
                __threadfence();
            }
        }
    } else if (warp < 2 + GATHER_WARPS + STATS_WARPS) {
        const int sw = warp - 2 - GATHER_WARPS;
        const int t = sw * 32 + lane;
        int s = 0;
        uint32_t ph = 0;
        for (int i = 0; i < G; i++) {
            mbar_wait(smem_u32(&bar_full[s]), ph);
            const uint4* sv = reinterpret_cast<const uint4*>(smem + (size_t)s * slot_bytes);
            float piv = 0.f, s1 = 0.f, s2 = 0.f;
            int cnt = 0;
            for (int v = t; v < nvec; v += STATS_THREADS) {
                const uint4 q = sv[v];
                if (cnt == 0) piv = bf_lo(q.x);
                const uint32_t w4[4] = {q.x, q.y, q.z, q.w};
#pragma unroll
                for (int e = 0; e < 4; e++) {
                    const float d0 = bf_lo(w4[e]) - piv;
                    const float d1 = bf_hi(w4[e]) - piv;
                    s1 += d0;
                    s2 = fmaf(d0, d0, s2);
                    s1 += d1;
                    s2 = fmaf(d1, d1, s2);
                }
                cnt += 8;
            }
            Stat st;
            st.n = (float)cnt;
            const float inv = cnt > 0 ? __fdividef(1.f, (float)cnt) : 0.f;
            const float dm = s1 * inv;
            st.mean = piv + dm;
            st.m2 = fmaxf(s2 - s1 * dm, 0.f);
            st = warp_merge(st);
            if (lane == 0) {
                float* sc = s_scratch + (i * STATS_WARPS + sw) * 4;
                sc[0] = st.n;
                sc[1] = st.mean;
                sc[2] = st.m2;
                mbar_arrive(smem_u32(&bar_stats[i]));
                if (sw == 0) TRACE(0, i);
            }
            if (++s == nslots) { s = 0; ph ^= 1u; }
        }
    } else {
        const int t = (warp - 2 - GATHER_WARPS - STATS_WARPS) * 32 + lane;
        int s = 0;
        uint32_t ph = 0;
        for (int j = 0; j < G; j++) {
            mbar_wait(smem_u32(&bar_ready[j]), 0u);
            mbar_wait(smem_u32(&bar_full[s]), ph);
            const float2 ms = s_stat[j];
            const long long ge0 = (long long)j * GROUP_ELEMS + (long long)my_start * (UNIT_BYTES / 2);
            const int c0 = (int)(ge0 >> HW_SHIFT);
            const int vb = (int)((((long long)(c0 + 1) << HW_SHIFT) - ge0) >> 3);
            const int c1 = (c0 + 1 < C) ? c0 + 1 : c0;
            const float a0 = ms.y * s_gamma[c0];
            const float d0 = fmaf(-ms.x, a0, s_beta[c0]);
            const float a1 = ms.y * s_gamma[c1];
            const float d1 = fmaf(-ms.x, a1, s_beta[c1]);
            const uint4* sv = reinterpret_cast<const uint4*>(smem + (size_t)s * slot_bytes);
            uint4* dst = reinterpret_cast<uint4*>(out + ge0);
#pragma unroll 4
            for (int v = t; v < nvec; v += NORM_THREADS) {
                const uint4 q = sv[v];
                const float a = (v < vb) ? a0 : a1;
                const float d = (v < vb) ? d0 : d1;
                uint4 r;
                r.x = pack_bf16(fmaf(bf_lo(q.x), a, d), fmaf(bf_hi(q.x), a, d));
                r.y = pack_bf16(fmaf(bf_lo(q.y), a, d), fmaf(bf_hi(q.y), a, d));
                r.z = pack_bf16(fmaf(bf_lo(q.z), a, d), fmaf(bf_hi(q.z), a, d));
                r.w = pack_bf16(fmaf(bf_lo(q.w), a, d), fmaf(bf_hi(q.w), a, d));
                dst[v] = r;
            }
            __syncwarp();
            if (lane == 0) mbar_arrive(smem_u32(&bar_empty[s]));
            if (t == 0) { *(volatile int*)s_norm_count = j + 1; TRACE(2, j); }
            if (++s == nslots) { s = 0; ph ^= 1u; }
        }
    }
}

}

extern "C" void kernel_launch(void* const* d_in, const int* in_sizes, int n_in, void* d_out,
                              int out_size) {
    (void)in_sizes; (void)n_in; (void)out_size;
    static int num_sms = 0;
    static int nslots = 0, slot_bytes = 0, smem_bytes = 0;
    if (num_sms == 0) {
        int dev = 0, max_smem = 0;
        cudaGetDevice(&dev);
        cudaDeviceGetAttribute(&num_sms, cudaDevAttrMultiProcessorCount, dev);
        cudaDeviceGetAttribute(&max_smem, cudaDevAttrMaxSharedMemoryPerBlockOptin, dev);
        if (num_sms > gn::MAX_POLL_CTAS) num_sms = gn::MAX_POLL_CTAS;
        const int max_units = (gn::GROUP_UNITS + num_sms - 1) / num_sms;
        slot_bytes = max_units * gn::UNIT_BYTES;
        const int tail_bytes = (2 * gn::MAX_SLOTS + 2 * gn::G) * 8 + gn::G * 8 + 2 * gn::C * 4 +
                               gn::G * gn::STATS_WARPS * 4 * 4 + 64;
        nslots = (max_smem - tail_bytes) / slot_bytes;
        if (nslots > gn::MAX_SLOTS) nslots = gn::MAX_SLOTS;
        smem_bytes = nslots * slot_bytes + tail_bytes;
        cudaFuncSetAttribute(gn::gn_kernel, cudaFuncAttributeMaxDynamicSharedMemorySize, smem_bytes);
    }
    const __nv_bfloat16* x = (const __nv_bfloat16*)d_in[0];
    const __nv_bfloat16* g = (const __nv_bfloat16*)d_in[1];
    const __nv_bfloat16* b = (const __nv_bfloat16*)d_in[2];
    __nv_bfloat16* out = (__nv_bfloat16*)d_out;
    gn::gn_kernel<<<num_sms, gn::NTHREADS, smem_bytes>>>(x, g, b, out, nslots, slot_bytes);
}
```

```cpp
#include <cuda_runtime.h>
#include <cuda_bf16.h>
#include <stdint.h>

namespace gn {

constexpr int G = 32;
constexpr int C = 448;
constexpr int CPG = C / G;
constexpr int HW = 16 * 4096;
constexpr int HW_SHIFT = 16;
constexpr long long GROUP_ELEMS = (long long)CPG * HW;
constexpr int UNIT_BYTES = 128;
constexpr int GROUP_UNITS = (int)(GROUP_ELEMS * 2 / UNIT_BYTES);
constexpr int MAX_CTAS = 512;
constexpr int MAX_SLOTS = 16;
constexpr int MAX_POLL_CTAS = 160;
#define GN_POLL_SLEEP 0

#define GN_GATHER 4
constexpr int GATHER_WARPS = GN_GATHER;
constexpr int STATS_WARPS = 4;
constexpr int NORM_WARPS = 8;
constexpr int NUM_WARPS = 2 + GATHER_WARPS + STATS_WARPS + NORM_WARPS;
constexpr int NTHREADS = NUM_WARPS * 32;
constexpr int STATS_THREADS = STATS_WARPS * 32;
constexpr int NORM_THREADS = NORM_WARPS * 32;
#define GN_INFLIGHT 4
constexpr int INFLIGHT = GN_INFLIGHT;
#define GN_INFLIGHT_LO 2
#define GN_LEAD_HI 8
constexpr int INFLIGHT_LO = GN_INFLIGHT_LO;
constexpr int LEAD_HI = GN_LEAD_HI;
constexpr unsigned long long WAIT_LIMIT_NS = 20000000ull;

__device__ ulonglong2 g_part[G][MAX_CTAS];
__device__ unsigned int g_epoch;
__device__ unsigned int g_done;
#define TRACE(k, j)

__device__ __forceinline__ uint32_t smem_u32(const void* p) {
    return (uint32_t)__cvta_generic_to_shared(p);
}
__device__ __forceinline__ void mbar_init(uint32_t bar, uint32_t count) {
    asm volatile("mbarrier.init.shared::cta.b64 [%0], %1;" ::"r"(bar), "r"(count) : "memory");
}
__device__ __forceinline__ void mbar_arrive_expect_tx(uint32_t bar, uint32_t bytes) {
    asm volatile("mbarrier.arrive.expect_tx.shared::cta.b64 _, [%0], %1;" ::"r"(bar), "r"(bytes)
                 : "memory");
}
__device__ __forceinline__ void mbar_arrive(uint32_t bar) {
    asm volatile("mbarrier.arrive.shared::cta.b64 _, [%0];" ::"r"(bar) : "memory");
}
__device__ __forceinline__ bool mbar_try_wait(uint32_t bar, uint32_t parity) {
    uint32_t ok;
    asm volatile(
        "{\n\t.reg .pred p;\n\t"
        "mbarrier.try_wait.parity.shared::cta.b64 p, [%1], %2;\n\t"
        "selp.u32 %0, 1, 0, p;\n\t}"
        : "=r"(ok)
        : "r"(bar), "r"(parity)
        : "memory");
    return ok != 0;
}
__device__ __forceinline__ unsigned long long global_ns() {
    unsigned long long t;
    asm volatile("mov.u64 %0, %globaltimer;" : "=l"(t));
    return t;
}
__device__ __forceinline__ void mbar_wait(uint32_t bar, uint32_t parity) {
    if (mbar_try_wait(bar, parity)) return;
    const unsigned long long t0 = global_ns();
    while (!mbar_try_wait(bar, parity)) {
        if (global_ns() - t0 > WAIT_LIMIT_NS) break;
    }
}
__device__ __forceinline__ ulonglong2 ld_relaxed_v2(const ulonglong2* p) {
    ulonglong2 v;
    asm volatile("ld.relaxed.gpu.global.v2.b64 {%0, %1}, [%2];" : "=l"(v.x), "=l"(v.y) : "l"(p) : "memory");
    return v;
}
__device__ __forceinline__ void st_relaxed_v2(ulonglong2* p, ulonglong2 v) {
    asm volatile("st.relaxed.gpu.global.v2.b64 [%0], {%1, %2};" ::"l"(p), "l"(v.x), "l"(v.y) : "memory");
}
__device__ __forceinline__ void bulk_load(uint32_t dst, const void* src, uint32_t bytes, uint32_t bar,
                                          uint64_t policy) {
    asm volatile(
        "cp.async.bulk.shared::cluster.global.mbarrier::complete_tx::bytes.L2::cache_hint "
        "[%0], [%1], %2, [%3], %4;" ::"r"(dst), "l"(src), "r"(bytes), "r"(bar), "l"(policy)
        : "memory");
}

struct Stat {
    float n, mean, m2;
};
__device__ __forceinline__ Stat merge(const Stat a, const Stat b) {
    Stat r;
    r.n = a.n + b.n;
    const float w = (r.n > 0.f) ? __fdividef(b.n, r.n) : 0.f;
    const float d = b.mean - a.mean;
    r.mean = fmaf(d, w, a.mean);
    r.m2 = a.m2 + b.m2 + d * d * a.n * w;
    return r;
}
__device__ __forceinline__ Stat warp_merge(Stat s) {
#pragma unroll
    for (int off = 16; off >= 1; off >>= 1) {
        Stat o;
        o.n = __shfl_xor_sync(0xffffffffu, s.n, off);
        o.mean = __shfl_xor_sync(0xffffffffu, s.mean, off);
        o.m2 = __shfl_xor_sync(0xffffffffu, s.m2, off);
        s = merge(s, o);
    }
    return s;
}

__device__ __forceinline__ float bf_lo(uint32_t u) { return __uint_as_float(u << 16); }
__device__ __forceinline__ float bf_hi(uint32_t u) { return __uint_as_float(u & 0xffff0000u); }
__device__ __forceinline__ uint32_t pack_bf16(float lo, float hi) {
    uint32_t r;
    asm("cvt.rn.bf16x2.f32 %0, %1, %2;" : "=r"(r) : "f"(hi), "f"(lo));
    return r;
}

__global__ void __launch_bounds__(NTHREADS, 1)
gn_kernel(const __nv_bfloat16* __restrict__ x, const __nv_bfloat16* __restrict__ gamma,
          const __nv_bfloat16* __restrict__ beta, __nv_bfloat16* __restrict__ out, int nslots,
          int slot_bytes) {
    extern __shared__ __align__(1024) unsigned char smem[];
    unsigned char* tail = smem + (size_t)nslots * slot_bytes;
    uint64_t* bar_full = reinterpret_cast<uint64_t*>(tail);
    uint64_t* bar_empty = bar_full + MAX_SLOTS;
    uint64_t* bar_ready = bar_empty + MAX_SLOTS;
    uint64_t* bar_stats = bar_ready + G;
    float2* s_stat = reinterpret_cast<float2*>(bar_stats + G);
    float* s_gamma = reinterpret_cast<float*>(s_stat + G);
    float* s_beta = s_gamma + C;
    float* s_scratch = s_beta + C;
    int* s_norm_count = reinterpret_cast<int*>(s_scratch + G * STATS_WARPS * 4);

    const int tid = threadIdx.x;
    const int warp = tid >> 5;
    const int lane = tid & 31;
    const int cta = blockIdx.x;
    const int ncta = gridDim.x;

    const int base = GROUP_UNITS / ncta;
    const int rem = GROUP_UNITS - base * ncta;
    const int my_units = base + (cta < rem ? 1 : 0);
    const int my_start = cta * base + (cta < rem ? cta : rem);
    const uint32_t my_bytes = (uint32_t)my_units * UNIT_BYTES;
    const int nvec = my_units * (UNIT_BYTES / 16);

    if (tid == 0) {
        TRACE(3, 0);
        *s_norm_count = 0;
        for (int s = 0; s < nslots; s++) {
            mbar_init(smem_u32(&bar_full[s]), 1);
            mbar_init(smem_u32(&bar_empty[s]), NORM_WARPS);
        }
        for (int j = 0; j < G; j++) {
            mbar_init(smem_u32(&bar_ready[j]), 1);
            mbar_init(smem_u32(&bar_stats[j]), STATS_WARPS);
        }
        asm volatile("fence.mbarrier_init.release.cluster;" ::: "memory");
        asm volatile("fence.proxy.async;" ::: "memory");
    }
    for (int c = tid; c < C; c += NTHREADS) {
        s_gamma[c] = __bfloat162float(gamma[c]);
        s_beta[c] = __bfloat162float(beta[c]);
    }
    __syncthreads();

    if (warp == 0) {
        if (lane == 0) {
            uint64_t policy;
            asm volatile("createpolicy.fractional.L2::evict_first.b64 %0, 1.0;" : "=l"(policy));
            int s = 0;
            uint32_t ph = 0;
            int sd = 0;
            uint32_t phd = 0;
            for (int i = 0; i < G; i++) {
                if (i >= nslots) mbar_wait(smem_u32(&bar_empty[s]), ph ^ 1u);
                if (i >= INFLIGHT) {
                    mbar_wait(smem_u32(&bar_full[sd]), phd);
                    if (++sd == nslots) { sd = 0; phd ^= 1u; }
                }
                mbar_arrive_expect_tx(smem_u32(&bar_full[s]), my_bytes);
                const unsigned char* src = reinterpret_cast<const unsigned char*>(x) +
                                           (size_t)i * (GROUP_ELEMS * 2) + (size_t)my_start * UNIT_BYTES;
                bulk_load(smem_u32(smem + (size_t)s * slot_bytes), src, my_bytes,
                          smem_u32(&bar_full[s]), policy);
                if (++s == nslots) { s = 0; ph ^= 1u; }
            }
        }
    } else if (warp == 1) {
        if (lane == 0) {
            const unsigned long long tag_hi =
                ((unsigned long long)(*(volatile unsigned int*)&g_epoch) + 1ull) << 32;
            for (int j = 0; j < G; j++) {
                mbar_wait(smem_u32(&bar_stats[j]), 0u);
                const float* sc = s_scratch + j * (STATS_WARPS * 4);
                Stat a = {sc[0], sc[1], sc[2]};
#pragma unroll
                for (int w = 1; w < STATS_WARPS; w++) {
                    Stat o = {sc[w * 4 + 0], sc[w * 4 + 1], sc[w * 4 + 2]};
                    a = merge(a, o);
                }
                ulonglong2 pv;
                pv.x = tag_hi | (unsigned long long)__float_as_uint(a.mean);
                pv.y = tag_hi | (unsigned long long)__float_as_uint(a.m2);
                st_relaxed_v2(&g_part[j][cta], pv);
            }
        }
    } else if (warp < 2 + GATHER_WARPS) {
        const int k = warp - 2;
        const unsigned long long tag = (unsigned long long)(*(volatile unsigned int*)&g_epoch) + 1ull;
        const unsigned long long tag_hi = tag << 32;
        for (int j = k; j < G; j += GATHER_WARPS) {
            mbar_wait(smem_u32(&bar_stats[j]), 0u);
            constexpr int PER_LANE = (MAX_POLL_CTAS + 31) / 32;
            ulonglong2 pv[PER_LANE];
            const unsigned long long tw0 = global_ns();
            while (true) {
                bool ok = true;
#pragma unroll
                for (int m = 0; m < PER_LANE; m++) {
                    const int c = lane + 32 * m;
                    if (c < ncta) pv[m] = ld_relaxed_v2(&g_part[j][c]);
                }
#pragma unroll
                for (int m = 0; m < PER_LANE; m++) {
                    const int c = lane + 32 * m;
                    if (c < ncta)
                        ok = ok && (((pv[m].x ^ tag_hi) | (pv[m].y ^ tag_hi)) >> 32) == 0ull;
                }
                if (__all_sync(0xffffffffu, ok)) break;
                if (global_ns() - tw0 > WAIT_LIMIT_NS) break;
            }
            float sn = 0.f, sm = 0.f;
#pragma unroll
            for (int m = 0; m < PER_LANE; m++) {
                const int c = lane + 32 * m;
                if (c < ncta) {
                    const float n = (float)((base + (c < rem ? 1 : 0)) * (UNIT_BYTES / 2));
                    sn += n;
                    sm = fmaf(n, __uint_as_float((unsigned)pv[m].x), sm);
                }
            }
#pragma unroll
            for (int off = 16; off >= 1; off >>= 1) {
                sn += __shfl_xor_sync(0xffffffffu, sn, off);
                sm += __shfl_xor_sync(0xffffffffu, sm, off);
            }
            const float gmean = sm / sn;
            float sq = 0.f;
#pragma unroll
            for (int m = 0; m < PER_LANE; m++) {
                const int c = lane + 32 * m;
                if (c < ncta) {
                    const float n = (float)((base + (c < rem ? 1 : 0)) * (UNIT_BYTES / 2));
                    const float d = __uint_as_float((unsigned)pv[m].x) - gmean;
                    sq += fmaf(n * d, d, __uint_as_float((unsigned)pv[m].y));
                }
            }
#pragma unroll
            for (int off = 16; off >= 1; off >>= 1) sq += __shfl_xor_sync(0xffffffffu, sq, off);
            Stat acc;
            acc.n = sn; acc.mean = gmean; acc.m2 = sq;
            if (lane == 0) {
                const float var = acc.m2 / acc.n;
                const float rstd = 1.0f / sqrtf(var + 1e-5f);
                s_stat[j] = make_float2(acc.mean, rstd);
                TRACE(1, j);
                mbar_arrive(smem_u32(&bar_ready[j]));
            }
        }
        __syncwarp();
        if (lane == 0) {
            const unsigned prev = atomicAdd(&g_done, 1u);
            if (prev == (unsigned)(ncta * GATHER_WARPS - 1)) {
                g_done = 0u;
                g_epoch = (unsigned)(tag);
                __threadfence();
            }
        }
    } else if (warp < 2 + GATHER_WARPS + STATS_WARPS) {
        const int sw = warp - 2 - GATHER_WARPS;
        const int t = sw * 32 + lane;
        int s = 0;
        uint32_t ph = 0;
        for (int i = 0; i < G; i++) {
            mbar_wait(smem_u32(&bar_full[s]), ph);
            const uint4* sv = reinterpret_cast<const uint4*>(smem + (size_t)s * slot_bytes);
            float piv = 0.f, s1 = 0.f, s2 = 0.f;
            int cnt = 0;
            for (int v = t; v < nvec; v += STATS_THREADS) {
                const uint4 q = sv[v];
                if (cnt == 0) piv = bf_lo(q.x);
                const uint32_t w4[4] = {q.x, q.y, q.z, q.w};
#pragma unroll
                for (int e = 0; e < 4; e++) {
                    const float d0 = bf_lo(w4[e]) - piv;
                    const float d1 = bf_hi(w4[e]) - piv;
                    s1 += d0;
                    s2 = fmaf(d0, d0, s2);
                    s1 += d1;
                    s2 = fmaf(d1, d1, s2);
                }
                cnt += 8;
            }
            Stat st;
            st.n = (float)cnt;
            const float inv = cnt > 0 ? __fdividef(1.f, (float)cnt) : 0.f;
            const float dm = s1 * inv;
            st.mean = piv + dm;
            st.m2 = fmaxf(s2 - s1 * dm, 0.f);
            st = warp_merge(st);
            if (lane == 0) {
                float* sc = s_scratch + (i * STATS_WARPS + sw) * 4;
                sc[0] = st.n;
                sc[1] = st.mean;
                sc[2] = st.m2;
                mbar_arrive(smem_u32(&bar_stats[i]));
                if (sw == 0) TRACE(0, i);
            }
            if (++s == nslots) { s = 0; ph ^= 1u; }
        }
    } else {
        const int t = (warp - 2 - GATHER_WARPS - STATS_WARPS) * 32 + lane;
        int s = 0;
        uint32_t ph = 0;
        for (int j = 0; j < G; j++) {
            mbar_wait(smem_u32(&bar_ready[j]), 0u);
            mbar_wait(smem_u32(&bar_full[s]), ph);
            const float2 ms = s_stat[j];
            const long long ge0 = (long long)j * GROUP_ELEMS + (long long)my_start * (UNIT_BYTES / 2);
            const int c0 = (int)(ge0 >> HW_SHIFT);
            const int vb = (int)((((long long)(c0 + 1) << HW_SHIFT) - ge0) >> 3);
            const int c1 = (c0 + 1 < C) ? c0 + 1 : c0;
            const float a0 = ms.y * s_gamma[c0];
            const float d0 = fmaf(-ms.x, a0, s_beta[c0]);
            const float a1 = ms.y * s_gamma[c1];
            const float d1 = fmaf(-ms.x, a1, s_beta[c1]);
            const uint4* sv = reinterpret_cast<const uint4*>(smem + (size_t)s * slot_bytes);
            uint4* dst = reinterpret_cast<uint4*>(out + ge0);
#pragma unroll 4
            for (int v = t; v < nvec; v += NORM_THREADS) {
                const uint4 q = sv[v];
                const float a = (v < vb) ? a0 : a1;
                const float d = (v < vb) ? d0 : d1;
                uint4 r;
                r.x = pack_bf16(fmaf(bf_lo(q.x), a, d), fmaf(bf_hi(q.x), a, d));
                r.y = pack_bf16(fmaf(bf_lo(q.y), a, d), fmaf(bf_hi(q.y), a, d));
                r.z = pack_bf16(fmaf(bf_lo(q.z), a, d), fmaf(bf_hi(q.z), a, d));
                r.w = pack_bf16(fmaf(bf_lo(q.w), a, d), fmaf(bf_hi(q.w), a, d));
                dst[v] = r;
            }
            __syncwarp();
            if (lane == 0) mbar_arrive(smem_u32(&bar_empty[s]));
            if (t == 0) { *(volatile int*)s_norm_count = j + 1; TRACE(2, j); }
            if (++s == nslots) { s = 0; ph ^= 1u; }
        }
    }
}

}

extern "C" void kernel_launch(void* const* d_in, const int* in_sizes, int n_in, void* d_out,
                              int out_size) {
    (void)in_sizes; (void)n_in; (void)out_size;
    static int num_sms = 0;
    static int nslots = 0, slot_bytes = 0, smem_bytes = 0;
    if (num_sms == 0) {
        int dev = 0, max_smem = 0;
        cudaGetDevice(&dev);
        cudaDeviceGetAttribute(&num_sms, cudaDevAttrMultiProcessorCount, dev);
        cudaDeviceGetAttribute(&max_smem, cudaDevAttrMaxSharedMemoryPerBlockOptin, dev);
        if (num_sms > gn::MAX_POLL_CTAS) num_sms = gn::MAX_POLL_CTAS;
        const int max_units = (gn::GROUP_UNITS + num_sms - 1) / num_sms;
        slot_bytes = max_units * gn::UNIT_BYTES;
        const int tail_bytes = (2 * gn::MAX_SLOTS + 2 * gn::G) * 8 + gn::G * 8 + 2 * gn::C * 4 +
                               gn::G * gn::STATS_WARPS * 4 * 4 + 64;
        nslots = (max_smem - tail_bytes) / slot_bytes;
        if (nslots > gn::MAX_SLOTS) nslots = gn::MAX_SLOTS;
        smem_bytes = nslots * slot_bytes + tail_bytes;
        cudaFuncSetAttribute(gn::gn_kernel, cudaFuncAttributeMaxDynamicSharedMemorySize, smem_bytes);
    }
    const __nv_bfloat16* x = (const __nv_bfloat16*)d_in[0];
    const __nv_bfloat16* g = (const __nv_bfloat16*)d_in[1];
    const __nv_bfloat16* b = (const __nv_bfloat16*)d_in[2];
    __nv_bfloat16* out = (__nv_bfloat16*)d_out;
    gn::gn_kernel<<<num_sms, gn::NTHREADS, smem_bytes>>>(x, g, b, out, nslots, slot_bytes);
}
```

```cpp
#include <cuda_runtime.h>
#include <cuda_bf16.h>
#include <stdint.h>

namespace gn {

constexpr int G = 32;
constexpr int C = 448;
constexpr int CPG = C / G;
constexpr int HW = 16 * 4096;
constexpr int HW_SHIFT = 16;
constexpr long long GROUP_ELEMS = (long long)CPG * HW;
constexpr int UNIT_BYTES = 128;
constexpr int GROUP_UNITS = (int)(GROUP_ELEMS * 2 / UNIT_BYTES);
constexpr int MAX_CTAS = 512;
constexpr int MAX_SLOTS = 16;
constexpr int MAX_POLL_CTAS = 160;
#define GN_POLL_SLEEP 0

#define GN_GATHER 4
constexpr int GATHER_WARPS = GN_GATHER;
constexpr int STATS_WARPS = 4;
constexpr int NORM_WARPS = 8;
constexpr int NUM_WARPS = 2 + GATHER_WARPS + STATS_WARPS + NORM_WARPS;
constexpr int NTHREADS = NUM_WARPS * 32;
constexpr int STATS_THREADS = STATS_WARPS * 32;
constexpr int NORM_THREADS = NORM_WARPS * 32;
#define GN_INFLIGHT 3
constexpr int INFLIGHT = GN_INFLIGHT;

constexpr unsigned long long WAIT_LIMIT_NS = 20000000ull;

__device__ ulonglong2 g_part[G][MAX_CTAS];
__device__ ulonglong2 g_final[G];
__device__ unsigned int g_epoch;
__device__ unsigned int g_done;
#define TRACE(k, j)

__device__ __forceinline__ uint32_t smem_u32(const void* p) {
    return (uint32_t)__cvta_generic_to_shared(p);
}
__device__ __forceinline__ void mbar_init(uint32_t bar, uint32_t count) {
    asm volatile("mbarrier.init.shared::cta.b64 [%0], %1;" ::"r"(bar), "r"(count) : "memory");
}
__device__ __forceinline__ void mbar_arrive_expect_tx(uint32_t bar, uint32_t bytes) {
    asm volatile("mbarrier.arrive.expect_tx.shared::cta.b64 _, [%0], %1;" ::"r"(bar), "r"(bytes)
                 : "memory");
}
__device__ __forceinline__ void mbar_arrive(uint32_t bar) {
    asm volatile("mbarrier.arrive.shared::cta.b64 _, [%0];" ::"r"(bar) : "memory");
}
__device__ __forceinline__ bool mbar_try_wait(uint32_t bar, uint32_t parity) {
    uint32_t ok;
    asm volatile(
        "{\n\t.reg .pred p;\n\t"
        "mbarrier.try_wait.parity.shared::cta.b64 p, [%1], %2;\n\t"
        "selp.u32 %0, 1, 0, p;\n\t}"
        : "=r"(ok)
        : "r"(bar), "r"(parity)
        : "memory");
    return ok != 0;
}
__device__ __forceinline__ unsigned long long global_ns() {
    unsigned long long t;
    asm volatile("mov.u64 %0, %globaltimer;" : "=l"(t));
    return t;
}
__device__ __forceinline__ void mbar_wait(uint32_t bar, uint32_t parity) {
    if (mbar_try_wait(bar, parity)) return;
    const unsigned long long t0 = global_ns();
    while (!mbar_try_wait(bar, parity)) {
        if (global_ns() - t0 > WAIT_LIMIT_NS) break;
    }
}
__device__ __forceinline__ ulonglong2 ld_relaxed_v2(const ulonglong2* p) {
    ulonglong2 v;
    asm volatile("ld.relaxed.gpu.global.v2.b64 {%0, %1}, [%2];" : "=l"(v.x), "=l"(v.y) : "l"(p) : "memory");
    return v;
}
__device__ __forceinline__ void st_relaxed_v2(ulonglong2* p, ulonglong2 v) {
    asm volatile("st.relaxed.gpu.global.v2.b64 [%0], {%1, %2};" ::"l"(p), "l"(v.x), "l"(v.y) : "memory");
}
__device__ __forceinline__ void bulk_load(uint32_t dst, const void* src, uint32_t bytes, uint32_t bar,
                                          uint64_t policy) {
    asm volatile(
        "cp.async.bulk.shared::cluster.global.mbarrier::complete_tx::bytes.L2::cache_hint "
        "[%0], [%1], %2, [%3], %4;" ::"r"(dst), "l"(src), "r"(bytes), "r"(bar), "l"(policy)
        : "memory");
}

struct Stat {
    float n, mean, m2;
};
__device__ __forceinline__ Stat merge(const Stat a, const Stat b) {
    Stat r;
    r.n = a.n + b.n;
    const float w = (r.n > 0.f) ? __fdividef(b.n, r.n) : 0.f;
    const float d = b.mean - a.mean;
    r.mean = fmaf(d, w, a.mean);
    r.m2 = a.m2 + b.m2 + d * d * a.n * w;
    return r;
}
__device__ __forceinline__ Stat warp_merge(Stat s) {
#pragma unroll
    for (int off = 16; off >= 1; off >>= 1) {
        Stat o;
        o.n = __shfl_xor_sync(0xffffffffu, s.n, off);
        o.mean = __shfl_xor_sync(0xffffffffu, s.mean, off);
        o.m2 = __shfl_xor_sync(0xffffffffu, s.m2, off);
        s = merge(s, o);
    }
    return s;
}

__device__ __forceinline__ float bf_lo(uint32_t u) { return __uint_as_float(u << 16); }
__device__ __forceinline__ float bf_hi(uint32_t u) { return __uint_as_float(u & 0xffff0000u); }
__device__ __forceinline__ uint32_t pack_bf16(float lo, float hi) {
    uint32_t r;
    asm("cvt.rn.bf16x2.f32 %0, %1, %2;" : "=r"(r) : "f"(hi), "f"(lo));
    return r;
}

__global__ void __launch_bounds__(NTHREADS, 1)
gn_kernel(const __nv_bfloat16* __restrict__ x, const __nv_bfloat16* __restrict__ gamma,
          const __nv_bfloat16* __restrict__ beta, __nv_bfloat16* __restrict__ out, int nslots,
          int slot_bytes) {
    extern __shared__ __align__(1024) unsigned char smem[];
    unsigned char* tail = smem + (size_t)nslots * slot_bytes;
    uint64_t* bar_full = reinterpret_cast<uint64_t*>(tail);
    uint64_t* bar_empty = bar_full + MAX_SLOTS;
    uint64_t* bar_ready = bar_empty + MAX_SLOTS;
    uint64_t* bar_stats = bar_ready + G;
    float2* s_stat = reinterpret_cast<float2*>(bar_stats + G);
    float* s_gamma = reinterpret_cast<float*>(s_stat + G);
    float* s_beta = s_gamma + C;
    float* s_scratch = s_beta + C;
    int* s_norm_count = reinterpret_cast<int*>(s_scratch + G * STATS_WARPS * 4);

    const int tid = threadIdx.x;
    const int warp = tid >> 5;
    const int lane = tid & 31;
    const int cta = blockIdx.x;
    const int ncta = gridDim.x;

    const int base = GROUP_UNITS / ncta;
    const int rem = GROUP_UNITS - base * ncta;
    const int my_units = base + (cta < rem ? 1 : 0);
    const int my_start = cta * base + (cta < rem ? cta : rem);
    const uint32_t my_bytes = (uint32_t)my_units * UNIT_BYTES;
    const int nvec = my_units * (UNIT_BYTES / 16);

    if (tid == 0) {
        TRACE(3, 0);
        *s_norm_count = 0;
        for (int s = 0; s < nslots; s++) {
            mbar_init(smem_u32(&bar_full[s]), 1);
            mbar_init(smem_u32(&bar_empty[s]), NORM_WARPS);
        }
        for (int j = 0; j < G; j++) {
            mbar_init(smem_u32(&bar_ready[j]), 1);
            mbar_init(smem_u32(&bar_stats[j]), STATS_WARPS);
        }
        asm volatile("fence.mbarrier_init.release.cluster;" ::: "memory");
        asm volatile("fence.proxy.async;" ::: "memory");
    }
    for (int c = tid; c < C; c += NTHREADS) {
        s_gamma[c] = __bfloat162float(gamma[c]);
        s_beta[c] = __bfloat162float(beta[c]);
    }
    __syncthreads();

    if (warp == 0) {
        if (lane == 0) {
            uint64_t policy;
            asm volatile("createpolicy.fractional.L2::evict_first.b64 %0, 1.0;" : "=l"(policy));
            int s = 0;
            uint32_t ph = 0;
            int sd = 0;
            uint32_t phd = 0;
            for (int i = 0; i < G; i++) {
                if (i >= nslots) mbar_wait(smem_u32(&bar_empty[s]), ph ^ 1u);
                if (i >= INFLIGHT) {
                    mbar_wait(smem_u32(&bar_full[sd]), phd);
                    if (++sd == nslots) { sd = 0; phd ^= 1u; }
                }
                mbar_arrive_expect_tx(smem_u32(&bar_full[s]), my_bytes);
                const unsigned char* src = reinterpret_cast<const unsigned char*>(x) +
                                           (size_t)i * (GROUP_ELEMS * 2) + (size_t)my_start * UNIT_BYTES;
                bulk_load(smem_u32(smem + (size_t)s * slot_bytes), src, my_bytes,
                          smem_u32(&bar_full[s]), policy);
                if (++s == nslots) { s = 0; ph ^= 1u; }
            }
        }
    } else if (warp == 1) {
        if (lane == 0) {
            const unsigned long long tag_hi =
                ((unsigned long long)(*(volatile unsigned int*)&g_epoch) + 1ull) << 32;
            for (int j = 0; j < G; j++) {
                mbar_wait(smem_u32(&bar_stats[j]), 0u);
                const float* sc = s_scratch + j * (STATS_WARPS * 4);
                Stat a = {sc[0], sc[1], sc[2]};
#pragma unroll
                for (int w = 1; w < STATS_WARPS; w++) {
                    Stat o = {sc[w * 4 + 0], sc[w * 4 + 1], sc[w * 4 + 2]};
                    a = merge(a, o);
                }
                ulonglong2 pv;
                pv.x = tag_hi | (unsigned long long)__float_as_uint(a.mean);
                pv.y = tag_hi | (unsigned long long)__float_as_uint(a.m2);
                st_relaxed_v2(&g_part[j][cta], pv);
            }
        }
    } else if (warp < 2 + GATHER_WARPS) {
        const int k = warp - 2;
        const unsigned long long tag = (unsigned long long)(*(volatile unsigned int*)&g_epoch) + 1ull;
        const unsigned long long tag_hi = tag << 32;
        for (int j = k; j < G; j += GATHER_WARPS) {
            mbar_wait(smem_u32(&bar_stats[j]), 0u);
            const int agg = (j * 37) % ncta;
            if (cta != agg) {
                const unsigned long long tw1 = global_ns();
                ulonglong2 fv;
                while (true) {
                    fv = ld_relaxed_v2(&g_final[j]);
                    if ((((fv.x ^ tag_hi) | (fv.y ^ tag_hi)) >> 32) == 0ull) break;
                    if (global_ns() - tw1 > WAIT_LIMIT_NS) break;
                }
                if (lane == 0) {
                    s_stat[j] = make_float2(__uint_as_float((unsigned)fv.x), __uint_as_float((unsigned)fv.y));
                    TRACE(1, j);
                    mbar_arrive(smem_u32(&bar_ready[j]));
                }
                continue;
            }
            constexpr int PER_LANE = (MAX_POLL_CTAS + 31) / 32;
            ulonglong2 pv[PER_LANE];
            const unsigned long long tw0 = global_ns();
            while (true) {
                bool ok = true;
#pragma unroll
                for (int m = 0; m < PER_LANE; m++) {
                    const int c = lane + 32 * m;
                    if (c < ncta) pv[m] = ld_relaxed_v2(&g_part[j][c]);
                }
#pragma unroll
                for (int m = 0; m < PER_LANE; m++) {
                    const int c = lane + 32 * m;
                    if (c < ncta)
                        ok = ok && (((pv[m].x ^ tag_hi) | (pv[m].y ^ tag_hi)) >> 32) == 0ull;
                }
                if (__all_sync(0xffffffffu, ok)) break;
                if (global_ns() - tw0 > WAIT_LIMIT_NS) break;
            }
            float sn = 0.f, sm = 0.f;
#pragma unroll
            for (int m = 0; m < PER_LANE; m++) {
                const int c = lane + 32 * m;
                if (c < ncta) {
                    const float n = (float)((base + (c < rem ? 1 : 0)) * (UNIT_BYTES / 2));
                    sn += n;
                    sm = fmaf(n, __uint_as_float((unsigned)pv[m].x), sm);
                }
            }
#pragma unroll
            for (int off = 16; off >= 1; off >>= 1) {
                sn += __shfl_xor_sync(0xffffffffu, sn, off);
                sm += __shfl_xor_sync(0xffffffffu, sm, off);
            }
            const float gmean = sm / sn;
            float sq = 0.f;
#pragma unroll
            for (int m = 0; m < PER_LANE; m++) {
                const int c = lane + 32 * m;
                if (c < ncta) {
                    const float n = (float)((base + (c < rem ? 1 : 0)) * (UNIT_BYTES / 2));
                    const float d = __uint_as_float((unsigned)pv[m].x) - gmean;
                    sq += fmaf(n * d, d, __uint_as_float((unsigned)pv[m].y));
                }
            }
#pragma unroll
            for (int off = 16; off >= 1; off >>= 1) sq += __shfl_xor_sync(0xffffffffu, sq, off);
            Stat acc;
            acc.n = sn; acc.mean = gmean; acc.m2 = sq;
            if (lane == 0) {
                const float var = acc.m2 / acc.n;
                const float rstd = 1.0f / sqrtf(var + 1e-5f);
                ulonglong2 fv;
                fv.x = tag_hi | (unsigned long long)__float_as_uint(acc.mean);
                fv.y = tag_hi | (unsigned long long)__float_as_uint(rstd);
                st_relaxed_v2(&g_final[j], fv);
                s_stat[j] = make_float2(acc.mean, rstd);
                TRACE(1, j);
                mbar_arrive(smem_u32(&bar_ready[j]));
            }
        }
        __syncwarp();
        if (lane == 0) {
            const unsigned prev = atomicAdd(&g_done, 1u);
            if (prev == (unsigned)(ncta * GATHER_WARPS - 1)) {
                g_done = 0u;
                g_epoch = (unsigned)(tag);
                __threadfence();
            }
        }
    } else if (warp < 2 + GATHER_WARPS + STATS_WARPS) {
        const int sw = warp - 2 - GATHER_WARPS;
        const int t = sw * 32 + lane;
        int s = 0;
        uint32_t ph = 0;
        for (int i = 0; i < G; i++) {
            mbar_wait(smem_u32(&bar_full[s]), ph);
            const uint4* sv = reinterpret_cast<const uint4*>(smem + (size_t)s * slot_bytes);
            float piv = 0.f, s1 = 0.f, s2 = 0.f;
            int cnt = 0;
            for (int v = t; v < nvec; v += STATS_THREADS) {
                const uint4 q = sv[v];
                if (cnt == 0) piv = bf_lo(q.x);
                const uint32_t w4[4] = {q.x, q.y, q.z, q.w};
#pragma unroll
                for (int e = 0; e < 4; e++) {
                    const float d0 = bf_lo(w4[e]) - piv;
                    const float d1 = bf_hi(w4[e]) - piv;
                    s1 += d0;
                    s2 = fmaf(d0, d0, s2);
                    s1 += d1;
                    s2 = fmaf(d1, d1, s2);
                }
                cnt += 8;
            }
            Stat st;
            st.n = (float)cnt;
            const float inv = cnt > 0 ? __fdividef(1.f, (float)cnt) : 0.f;
            const float dm = s1 * inv;
            st.mean = piv + dm;
            st.m2 = fmaxf(s2 - s1 * dm, 0.f);
            st = warp_merge(st);
            if (lane == 0) {
                float* sc = s_scratch + (i * STATS_WARPS + sw) * 4;
                sc[0] = st.n;
                sc[1] = st.mean;
                sc[2] = st.m2;
                mbar_arrive(smem_u32(&bar_stats[i]));
                if (sw == 0) TRACE(0, i);
            }
            if (++s == nslots) { s = 0; ph ^= 1u; }
        }
    } else {
        const int t = (warp - 2 - GATHER_WARPS - STATS_WARPS) * 32 + lane;
        int s = 0;
        uint32_t ph = 0;
        for (int j = 0; j < G; j++) {
            mbar_wait(smem_u32(&bar_ready[j]), 0u);
            mbar_wait(smem_u32(&bar_full[s]), ph);
            const float2 ms = s_stat[j];
            const long long ge0 = (long long)j * GROUP_ELEMS + (long long)my_start * (UNIT_BYTES / 2);
            const int c0 = (int)(ge0 >> HW_SHIFT);
            const int vb = (int)((((long long)(c0 + 1) << HW_SHIFT) - ge0) >> 3);
            const int c1 = (c0 + 1 < C) ? c0 + 1 : c0;
            const float a0 = ms.y * s_gamma[c0];
            const float d0 = fmaf(-ms.x, a0, s_beta[c0]);
            const float a1 = ms.y * s_gamma[c1];
            const float d1 = fmaf(-ms.x, a1, s_beta[c1]);
            const uint4* sv = reinterpret_cast<const uint4*>(smem + (size_t)s * slot_bytes);
            uint4* dst = reinterpret_cast<uint4*>(out + ge0);
#pragma unroll 4
            for (int v = t; v < nvec; v += NORM_THREADS) {
                const uint4 q = sv[v];
                const float a = (v < vb) ? a0 : a1;
                const float d = (v < vb) ? d0 : d1;
                uint4 r;
                r.x = pack_bf16(fmaf(bf_lo(q.x), a, d), fmaf(bf_hi(q.x), a, d));
                r.y = pack_bf16(fmaf(bf_lo(q.y), a, d), fmaf(bf_hi(q.y), a, d));
                r.z = pack_bf16(fmaf(bf_lo(q.z), a, d), fmaf(bf_hi(q.z), a, d));
                r.w = pack_bf16(fmaf(bf_lo(q.w), a, d), fmaf(bf_hi(q.w), a, d));
                dst[v] = r;
            }
            __syncwarp();
            if (lane == 0) mbar_arrive(smem_u32(&bar_empty[s]));
            if (t == 0) { *(volatile int*)s_norm_count = j + 1; TRACE(2, j); }
            if (++s == nslots) { s = 0; ph ^= 1u; }
        }
    }
}

}

extern "C" void kernel_launch(void* const* d_in, const int* in_sizes, int n_in, void* d_out,
                              int out_size) {
    (void)in_sizes; (void)n_in; (void)out_size;
    static int num_sms = 0;
    static int nslots = 0, slot_bytes = 0, smem_bytes = 0;
    if (num_sms == 0) {
        int dev = 0, max_smem = 0;
        cudaGetDevice(&dev);
        cudaDeviceGetAttribute(&num_sms, cudaDevAttrMultiProcessorCount, dev);
        cudaDeviceGetAttribute(&max_smem, cudaDevAttrMaxSharedMemoryPerBlockOptin, dev);
        if (num_sms > gn::MAX_POLL_CTAS) num_sms = gn::MAX_POLL_CTAS;
        const int max_units = (gn::GROUP_UNITS + num_sms - 1) / num_sms;
        slot_bytes = max_units * gn::UNIT_BYTES;
        const int tail_bytes = (2 * gn::MAX_SLOTS + 2 * gn::G) * 8 + gn::G * 8 + 2 * gn::C * 4 +
                               gn::G * gn::STATS_WARPS * 4 * 4 + 64;
        nslots = (max_smem - tail_bytes) / slot_bytes;
        if (nslots > gn::MAX_SLOTS) nslots = gn::MAX_SLOTS;
        smem_bytes = nslots * slot_bytes + tail_bytes;
        cudaFuncSetAttribute(gn::gn_kernel, cudaFuncAttributeMaxDynamicSharedMemorySize, smem_bytes);
    }
    const __nv_bfloat16* x = (const __nv_bfloat16*)d_in[0];
    const __nv_bfloat16* g = (const __nv_bfloat16*)d_in[1];
    const __nv_bfloat16* b = (const __nv_bfloat16*)d_in[2];
    __nv_bfloat16* out = (__nv_bfloat16*)d_out;
    gn::gn_kernel<<<num_sms, gn::NTHREADS, smem_bytes>>>(x, g, b, out, nslots, slot_bytes);
}
```
